```python
import torch

def _softmax(x, axis=-1):
    return torch.softmax(x, dim=axis)
def _gelu(x):
    return torch.nn.functional.gelu(x, approximate="tanh")
def _silu(x):
    return torch.nn.functional.silu(x)
def _sigmoid(x):
    return torch.sigmoid(x)
def _layernorm(x, axis=-1, eps=1e-5):
    m = x.mean(dim=axis, keepdim=True)
    v = x.var(dim=axis, keepdim=True, unbiased=False)
    return (x - m) / torch.sqrt(v + eps)
def _scatter_add(tgt, idx, src, axis=0):
    return tgt.clone().index_add_(axis, idx, src)
def _segment_sum(src, seg, n):
    out = torch.zeros((n,) + src.shape[1:], dtype=src.dtype)
    return out.index_add_(0, seg, src)
def _pad(x, pw):
    flat = tuple(v for pair in reversed(pw) for v in pair)
    return torch.nn.functional.pad(x, flat)

kernel_name = 'sequential_preLN__sliding_local_dilated__glu_gated_swiglu__prompt'

def setup_inputs():

    _w = (lambda a: (lambda t: t.to(torch.bfloat16) if t.is_floating_point() else t)(torch.as_tensor(a)))
    def _A_setup():
        B, S, D = 1, 2048, 512
        return {
            "x": _w((lambda *s: torch.randn(*s, dtype=torch.bfloat16) * 0.05)(B, S, D)),
            "wqkv": _w((lambda *s: torch.randn(*s, dtype=torch.bfloat16) * 0.05)(D, 3 * D)),
            "wo": _w((lambda *s: torch.randn(*s, dtype=torch.bfloat16) * 0.05)(D, D)),
        }
    _A_in = _A_setup()

    def _B_setup():
        B, S, D, F = 1, 2048, 512, 1792
        return {
            "x": _w((lambda *s: torch.randn(*s, dtype=torch.bfloat16) * 0.05)(B, S, D)),
            "w1": _w((lambda *s: torch.randn(*s, dtype=torch.bfloat16) * 0.8)(D, F) * (2.0 / D) ** 0.5),
            "w3": _w((lambda *s: torch.randn(*s, dtype=torch.bfloat16) * 0.8)(D, F) * (2.0 / D) ** 0.5),
            "w2": _w((lambda *s: torch.randn(*s, dtype=torch.bfloat16) * 0.8)(F, D) * (2.0 / F) ** 0.5),
        }
    _B_in = _B_setup()

    return {
        "A_x": _A_in["x"],
        "A_wqkv": _A_in["wqkv"],
        "A_wo": _A_in["wo"],
        "B_x": _B_in["x"],
        "B_w1": _B_in["w1"],
        "B_w3": _B_in["w3"],
        "B_w2": _B_in["w2"],
    }

def reference(A_x, A_wqkv, A_wo, B_x, B_w1, B_w3, B_w2):
    def _A_ref(x, wqkv, wo):
        B, S, D = x.shape
        H = 32; Dh = D // H
        W, dil = 8, 2
        qkv = (lambda x, *d: x.permute(*d))((x @ wqkv).reshape(B, S, 3, H, Dh), 2, 0, 3, 1, 4)
        q, k, v = qkv[0], qkv[1], qkv[2]
        scale = Dh ** -0.5
        pos = torch.arange(S)
        off = torch.arange(W) * dil
        idx = pos[:, None] - off[None, :]
        mask = idx >= 0
        idx_c = torch.where(mask, idx, 0).reshape(-1)
        kg = k[:, :, idx_c, :].reshape(B, H, S, W, Dh)
        vg = v[:, :, idx_c, :].reshape(B, H, S, W, Dh)
        logits = torch.einsum("bhsd,bhswd->bhsw", q, kg) * scale
        logits = torch.where(mask[None, None, :, :], logits, -1e9)
        attn = _softmax(logits, axis=-1)
        o = torch.einsum("bhsw,bhswd->bhsd", attn, vg)
        return (lambda x, *d: x.permute(*d))(o, 0, 2, 1, 3).reshape(B, S, D) @ wo

    def _B_ref(x, w1, w3, w2):
        gate = torch.einsum("bsd,df->bsf", x, w1)
        up = torch.einsum("bsd,df->bsf", x, w3)
        h = _silu(gate) * up
        out = torch.einsum("bsf,fd->bsd", h, w2)
        return out

    x = A_x
    h = x + _A_ref(_layernorm(x, axis=-1), A_wqkv, A_wo)
    h2 = h + _B_ref(_layernorm(h, axis=-1), B_w1, B_w3, B_w2)
    return h2
```

```cpp
#include <cuda_runtime.h>
#include <cuda_bf16.h>
#include <cuda.h>
#include <stdint.h>

namespace {

constexpr uint32_t SM_ACT = 0, SM_RING = 131072, SM_CSQ = 229376, SM_CS13 = SM_CSQ + 768, SM_BAR = SM_CSQ + 2560;
constexpr uint32_t SMEM_BYTES = 232448;
constexpr uint32_t SB = 1024;
enum { B_XF = 0, B_WF = 8, B_WE = 12, B_OF = 16, B_GF = 17, B_GE = 23, B_DF = 29, B_DE = 41, B_CS1 = 42, B_CS2 = 43, B_HX = 44, B_WD = 45, B_N = 46 };
constexpr uint32_t TAGM = 0x00010001u;
#define LOOKAHEAD 3
#define XPROMO CU_TENSOR_MAP_L2_PROMOTION_L2_128B
#define WGOFF 1
#define GATH 1
#define MAP 0
#define XAHEAD 2
#define DLA 3
#define QDEF 2
#define GQ_AT 7
#define TMPF 0
#define CLR 1
constexpr int SPIN_LIMIT = 1 << 16;

__device__ uint4 g_obox[128 * 8 * 4 * 32];
__device__ uint4 g_hbox[128 * 8 * 4 * 32];
__device__ uint4 g_pbox[128 * 8 * 14 * 32];
__device__ uint4 g_part[128 * 8 * 4 * 32];
__device__ uint4 g_halo[128 * 2 * 4 * 32];
__device__ uint4 g_stat[128 * 16 + 128 * 128];
__device__ uint4 g_csq[128 * 48];
__device__ uint4 g_cs13[128 * 112];
__device__ unsigned g_epoch[132];
#define PROF(slot)
#define PROFD(slot)
#define PROFT(slot)
#define PROF_INIT
#define PROF_START
#define PROF_END

struct Params {
    CUtensorMap tmX, tmQKV, tmWO, tmW1, tmW3, tmW1h, tmW3h, tmW2, tmW2a;
    const __nv_bfloat16 *x, *wqkv, *wo, *w1, *w3, *w2;
    __nv_bfloat16* out;
    int by_smid;
    uint64_t dB128[4], dB64, dA[2];
};

__device__ __forceinline__ void mbar_init(uint32_t bar, uint32_t cnt) { asm volatile("mbarrier.init.shared::cta.b64 [%0], %1;" ::"r"(bar), "r"(cnt) : "memory"); }
__device__ __forceinline__ void mbar_arrive(uint32_t bar) { asm volatile("mbarrier.arrive.shared::cta.b64 _, [%0];" ::"r"(bar) : "memory"); }
__device__ __forceinline__ void mbar_wait(uint32_t bar, uint32_t parity) {
    asm volatile("{\n.reg .pred p;\n.reg .u32 n;\nmov.u32 n, 0;\n"
                 "LW:\nmbarrier.try_wait.parity.shared::cta.b64 p, [%0], %1;\n@p bra LD;\n"
                 "add.u32 n, n, 1;\nsetp.lt.u32 p, n, 262144;\n@p bra LW;\nLD:\n}" ::"r"(bar), "r"(parity) : "memory");
}
__device__ __forceinline__ void tma2d_e(uint32_t dst, const CUtensorMap* tm, int c0, int c1, uint32_t bar) {
    asm volatile("{\n.reg .pred p;\nelect.sync _|p, 0xffffffff;\n"
                 "@p cp.async.bulk.tensor.2d.shared::cluster.global.mbarrier::complete_tx::bytes [%0], [%1, {%3, %4}], [%2];\n}"
                 ::"r"(dst), "l"(tm), "r"(bar), "r"(c0), "r"(c1) : "memory");
}
__device__ __forceinline__ void tma3d_e(uint32_t dst, const CUtensorMap* tm, int c0, int c1, uint32_t bar) {
    asm volatile("{\n.reg .pred p;\nelect.sync _|p, 0xffffffff;\n"
                 "@p cp.async.bulk.tensor.3d.shared::cluster.global.mbarrier::complete_tx::bytes [%0], [%1, {%3, %4, 0}], [%2];\n}"
                 ::"r"(dst), "l"(tm), "r"(bar), "r"(c0), "r"(c1) : "memory");
}
__device__ __forceinline__ void mbar_expect_e(uint32_t bar, uint32_t bytes) {
    asm volatile("{\n.reg .pred p;\nelect.sync _|p, 0xffffffff;\n@p mbarrier.arrive.expect_tx.shared::cta.b64 _, [%0], %1;\n}" ::"r"(bar), "r"(bytes) : "memory");
}
__device__ __forceinline__ void wg_fence() { asm volatile("wgmma.fence.sync.aligned;" ::: "memory"); }
__device__ __forceinline__ void wg_commit() { asm volatile("wgmma.commit_group.sync.aligned;" ::: "memory"); }
template <int N> __device__ __forceinline__ void wg_wait() { asm volatile("wgmma.wait_group.sync.aligned %0;" ::"n"(N) : "memory"); }
template <int N> __device__ __forceinline__ void reg_fence(float* d) {
#pragma unroll
    for (int i = 0; i < N; i++) asm volatile("" : "+f"(d[i])::"memory");
}
__device__ __forceinline__ void ldsm4(uint32_t (&r)[4], uint32_t addr) {
    asm volatile("ldmatrix.sync.aligned.m8n8.x4.shared.b16 {%0,%1,%2,%3}, [%4];" : "=r"(r[0]), "=r"(r[1]), "=r"(r[2]), "=r"(r[3]) : "r"(addr) : "memory");
}
__device__ __forceinline__ void stsm4(uint32_t addr, const uint32_t (&r)[4]) {
    asm volatile("stmatrix.sync.aligned.m8n8.x4.shared.b16 [%0], {%1,%2,%3,%4};" ::"r"(addr), "r"(r[0]), "r"(r[1]), "r"(r[2]), "r"(r[3]) : "memory");
}
__device__ __forceinline__ uint32_t movm(uint32_t a) { uint32_t d; asm volatile("movmatrix.sync.aligned.m8n8.trans.b16 %0, %1;" : "=r"(d) : "r"(a)); return d; }
__device__ __forceinline__ void mma16(float (&c)[4], uint32_t a0, uint32_t a1, uint32_t a2, uint32_t a3, uint32_t b0, uint32_t b1) {
    asm volatile("mma.sync.aligned.m16n8k16.row.col.f32.bf16.bf16.f32 {%0,%1,%2,%3}, {%4,%5,%6,%7}, {%8,%9}, {%0,%1,%2,%3};"
                 : "+f"(c[0]), "+f"(c[1]), "+f"(c[2]), "+f"(c[3]) : "r"(a0), "r"(a1), "r"(a2), "r"(a3), "r"(b0), "r"(b1));
}
__device__ __forceinline__ void mma8(float (&c)[4], uint32_t a0, uint32_t a1, uint32_t b0) {
    asm volatile("mma.sync.aligned.m16n8k8.row.col.f32.bf16.bf16.f32 {%0,%1,%2,%3}, {%4,%5}, {%6}, {%0,%1,%2,%3};"
                 : "+f"(c[0]), "+f"(c[1]), "+f"(c[2]), "+f"(c[3]) : "r"(a0), "r"(a1), "r"(b0));
}
__device__ __forceinline__ uint32_t pack2(float lo, float hi) { uint32_t r; asm("cvt.rn.bf16x2.f32 %0, %1, %2;" : "=r"(r) : "f"(hi), "f"(lo)); return r; }
__device__ __forceinline__ float blo(uint32_t v) { return __uint_as_float(v << 16); }
__device__ __forceinline__ float bhi(uint32_t v) { return __uint_as_float(v & 0xffff0000u); }
__device__ __forceinline__ float ex2(float x) { float r; asm("ex2.approx.ftz.f32 %0, %1;" : "=f"(r) : "f"(x)); return r; }
__device__ __forceinline__ float rcp(float x) { float r; asm("rcp.approx.ftz.f32 %0, %1;" : "=f"(r) : "f"(x)); return r; }
__device__ __forceinline__ float rsq(float x) { float r; asm("rsqrt.approx.ftz.f32 %0, %1;" : "=f"(r) : "f"(x)); return r; }
__device__ __forceinline__ float2 lds64(uint32_t a) { float2 v; asm volatile("ld.shared.v2.f32 {%0,%1}, [%2];" : "=f"(v.x), "=f"(v.y) : "r"(a)); return v; }
__device__ __forceinline__ void lds128(uint32_t (&v)[4], uint32_t a) {
    asm volatile("ld.shared.v4.u32 {%0,%1,%2,%3}, [%4];" : "=r"(v[0]), "=r"(v[1]), "=r"(v[2]), "=r"(v[3]) : "r"(a) : "memory");
}
__device__ __forceinline__ void cp_wait(int n) {
    if (n == 0) asm volatile("cp.async.wait_group 0;" ::: "memory");
    else if (n == 1) asm volatile("cp.async.wait_group 1;" ::: "memory");
    else if (n == 2) asm volatile("cp.async.wait_group 2;" ::: "memory");
    else asm volatile("cp.async.wait_group 3;" ::: "memory");
}
__device__ __forceinline__ void ldbox(uint32_t (&r)[4], const uint4* p) {
    asm volatile("{\n.reg .b128 t;\nld.relaxed.gpu.global.b128 t, [%4];\nmov.b128 {%0,%1,%2,%3}, t;\n}"
                 : "=r"(r[0]), "=r"(r[1]), "=r"(r[2]), "=r"(r[3]) : "l"(p) : "memory");
}
__device__ __forceinline__ void stbox(uint4* p, uint32_t a, uint32_t b, uint32_t c, uint32_t d) {
    asm volatile("{\n.reg .b128 t;\nmov.b128 t, {%1,%2,%3,%4};\nst.relaxed.gpu.global.b128 [%0], t;\n}" ::"l"(p), "r"(a), "r"(b), "r"(c), "r"(d) : "memory");
}
__device__ __forceinline__ void ldgroup(uint32_t (&v)[4][4], const uint4* p) {
#pragma unroll
    for (int i = 0; i < 4; i++) ldbox(v[i], p + i * 32);
}
__device__ __forceinline__ void stgroup(uint4* p, const uint32_t (&v)[4][4], uint32_t tag) {
#pragma unroll
    for (int i = 0; i < 4; i++) stbox(p + i * 32, (v[i][0] & ~TAGM) | tag, v[i][1], v[i][2], v[i][3]);
}
__device__ __forceinline__ void chkgroup(uint32_t (&v)[4][4], const uint4* p, uint32_t tag) {
    int n = 0;
    while (true) {
        uint32_t bad = ((v[0][0] ^ tag) | (v[1][0] ^ tag) | (v[2][0] ^ tag) | (v[3][0] ^ tag)) & TAGM;
        if (!__any_sync(0xffffffffu, bad != 0) || ++n > SPIN_LIMIT) break;
        ldgroup(v, p);
    }
}
__device__ __forceinline__ void pollgroup(uint32_t (&v)[4][4], const uint4* p, uint32_t tag) {
    int n = 0;
    while (true) {
        ldgroup(v, p);
        uint32_t bad = ((v[0][0] ^ tag) | (v[1][0] ^ tag) | (v[2][0] ^ tag) | (v[3][0] ^ tag)) & TAGM;
        if (!__any_sync(0xffffffffu, bad != 0) || ++n > SPIN_LIMIT) break;
    }
}
__device__ __forceinline__ void chk2(uint32_t (&v)[2][4], const uint4* p, uint32_t tag) {
    int n = 0;
    while (true) {
        uint32_t bad = ((v[0][0] ^ tag) | (v[1][0] ^ tag)) & TAGM;
        if (!__any_sync(0xffffffffu, bad != 0) || ++n > SPIN_LIMIT) break;
        ldbox(v[0], p); ldbox(v[1], p + 32);
    }
}
template <bool ACC>
__device__ __forceinline__ void wgmma_rs_n64(float* d, const uint32_t (&a)[4], uint64_t db) {
    if constexpr (ACC) {
        asm volatile("wgmma.mma_async.sync.aligned.m64n64k16.f32.bf16.bf16 "
            "{%0, %1, %2, %3, %4, %5, %6, %7, %8, %9, %10, %11, %12, %13, %14, %15, %16, %17, %18, %19, %20, %21, %22, %23, %24, %25, %26, %27, %28, %29, %30, %31}, "
            "{%32, %33, %34, %35}, %36, 1, 1, 1, 1;"
            : "+f"(d[0]), "+f"(d[1]), "+f"(d[2]), "+f"(d[3]), "+f"(d[4]), "+f"(d[5]), "+f"(d[6]), "+f"(d[7]),
              "+f"(d[8]), "+f"(d[9]), "+f"(d[10]), "+f"(d[11]), "+f"(d[12]), "+f"(d[13]), "+f"(d[14]), "+f"(d[15]),
              "+f"(d[16]), "+f"(d[17]), "+f"(d[18]), "+f"(d[19]), "+f"(d[20]), "+f"(d[21]), "+f"(d[22]), "+f"(d[23]),
              "+f"(d[24]), "+f"(d[25]), "+f"(d[26]), "+f"(d[27]), "+f"(d[28]), "+f"(d[29]), "+f"(d[30]), "+f"(d[31])
            : "r"(a[0]), "r"(a[1]), "r"(a[2]), "r"(a[3]), "l"(db));
    } else {
        asm volatile("wgmma.mma_async.sync.aligned.m64n64k16.f32.bf16.bf16 "
            "{%0, %1, %2, %3, %4, %5, %6, %7, %8, %9, %10, %11, %12, %13, %14, %15, %16, %17, %18, %19, %20, %21, %22, %23, %24, %25, %26, %27, %28, %29, %30, %31}, "
            "{%32, %33, %34, %35}, %36, 0, 1, 1, 1;"
            : "=f"(d[0]), "=f"(d[1]), "=f"(d[2]), "=f"(d[3]), "=f"(d[4]), "=f"(d[5]), "=f"(d[6]), "=f"(d[7]),
              "=f"(d[8]), "=f"(d[9]), "=f"(d[10]), "=f"(d[11]), "=f"(d[12]), "=f"(d[13]), "=f"(d[14]), "=f"(d[15]),
              "=f"(d[16]), "=f"(d[17]), "=f"(d[18]), "=f"(d[19]), "=f"(d[20]), "=f"(d[21]), "=f"(d[22]), "=f"(d[23]),
              "=f"(d[24]), "=f"(d[25]), "=f"(d[26]), "=f"(d[27]), "=f"(d[28]), "=f"(d[29]), "=f"(d[30]), "=f"(d[31])
            : "r"(a[0]), "r"(a[1]), "r"(a[2]), "r"(a[3]), "l"(db));
    }
}
template <bool ACC>
__device__ __forceinline__ void wgmma_rs_n128(float* d, const uint32_t (&a)[4], uint64_t db) {
    if constexpr (ACC) {
        asm volatile("wgmma.mma_async.sync.aligned.m64n128k16.f32.bf16.bf16 "
            "{%0, %1, %2, %3, %4, %5, %6, %7, %8, %9, %10, %11, %12, %13, %14, %15, %16, %17, %18, %19, %20, %21, %22, %23, %24, %25, %26, %27, %28, %29, %30, %31, %32, %33, %34, %35, %36, %37, %38, %39, %40, %41, %42, %43, %44, %45, %46, %47, %48, %49, %50, %51, %52, %53, %54, %55, %56, %57, %58, %59, %60, %61, %62, %63}, "
            "{%64, %65, %66, %67}, %68, 1, 1, 1, 1;"
            : "+f"(d[0]), "+f"(d[1]), "+f"(d[2]), "+f"(d[3]), "+f"(d[4]), "+f"(d[5]), "+f"(d[6]), "+f"(d[7]),
              "+f"(d[8]), "+f"(d[9]), "+f"(d[10]), "+f"(d[11]), "+f"(d[12]), "+f"(d[13]), "+f"(d[14]), "+f"(d[15]),
              "+f"(d[16]), "+f"(d[17]), "+f"(d[18]), "+f"(d[19]), "+f"(d[20]), "+f"(d[21]), "+f"(d[22]), "+f"(d[23]),
              "+f"(d[24]), "+f"(d[25]), "+f"(d[26]), "+f"(d[27]), "+f"(d[28]), "+f"(d[29]), "+f"(d[30]), "+f"(d[31]),
              "+f"(d[32]), "+f"(d[33]), "+f"(d[34]), "+f"(d[35]), "+f"(d[36]), "+f"(d[37]), "+f"(d[38]), "+f"(d[39]),
              "+f"(d[40]), "+f"(d[41]), "+f"(d[42]), "+f"(d[43]), "+f"(d[44]), "+f"(d[45]), "+f"(d[46]), "+f"(d[47]),
              "+f"(d[48]), "+f"(d[49]), "+f"(d[50]), "+f"(d[51]), "+f"(d[52]), "+f"(d[53]), "+f"(d[54]), "+f"(d[55]),
              "+f"(d[56]), "+f"(d[57]), "+f"(d[58]), "+f"(d[59]), "+f"(d[60]), "+f"(d[61]), "+f"(d[62]), "+f"(d[63])
            : "r"(a[0]), "r"(a[1]), "r"(a[2]), "r"(a[3]), "l"(db));
    } else {
        asm volatile("wgmma.mma_async.sync.aligned.m64n128k16.f32.bf16.bf16 "
            "{%0, %1, %2, %3, %4, %5, %6, %7, %8, %9, %10, %11, %12, %13, %14, %15, %16, %17, %18, %19, %20, %21, %22, %23, %24, %25, %26, %27, %28, %29, %30, %31, %32, %33, %34, %35, %36, %37, %38, %39, %40, %41, %42, %43, %44, %45, %46, %47, %48, %49, %50, %51, %52, %53, %54, %55, %56, %57, %58, %59, %60, %61, %62, %63}, "
            "{%64, %65, %66, %67}, %68, 0, 1, 1, 1;"
            : "=f"(d[0]), "=f"(d[1]), "=f"(d[2]), "=f"(d[3]), "=f"(d[4]), "=f"(d[5]), "=f"(d[6]), "=f"(d[7]),
              "=f"(d[8]), "=f"(d[9]), "=f"(d[10]), "=f"(d[11]), "=f"(d[12]), "=f"(d[13]), "=f"(d[14]), "=f"(d[15]),
              "=f"(d[16]), "=f"(d[17]), "=f"(d[18]), "=f"(d[19]), "=f"(d[20]), "=f"(d[21]), "=f"(d[22]), "=f"(d[23]),
              "=f"(d[24]), "=f"(d[25]), "=f"(d[26]), "=f"(d[27]), "=f"(d[28]), "=f"(d[29]), "=f"(d[30]), "=f"(d[31]),
              "=f"(d[32]), "=f"(d[33]), "=f"(d[34]), "=f"(d[35]), "=f"(d[36]), "=f"(d[37]), "=f"(d[38]), "=f"(d[39]),
              "=f"(d[40]), "=f"(d[41]), "=f"(d[42]), "=f"(d[43]), "=f"(d[44]), "=f"(d[45]), "=f"(d[46]), "=f"(d[47]),
              "=f"(d[48]), "=f"(d[49]), "=f"(d[50]), "=f"(d[51]), "=f"(d[52]), "=f"(d[53]), "=f"(d[54]), "=f"(d[55]),
              "=f"(d[56]), "=f"(d[57]), "=f"(d[58]), "=f"(d[59]), "=f"(d[60]), "=f"(d[61]), "=f"(d[62]), "=f"(d[63])
            : "r"(a[0]), "r"(a[1]), "r"(a[2]), "r"(a[3]), "l"(db));
    }
}
template <bool ACC>
__device__ __forceinline__ void wgmma_ss_n64(float* d, uint64_t da, uint64_t db) {
    if constexpr (ACC) {
        asm volatile("wgmma.mma_async.sync.aligned.m64n64k16.f32.bf16.bf16 "
            "{%0, %1, %2, %3, %4, %5, %6, %7, %8, %9, %10, %11, %12, %13, %14, %15, %16, %17, %18, %19, %20, %21, %22, %23, %24, %25, %26, %27, %28, %29, %30, %31}, "
            "%32, %33, 1, 1, 1, 0, 1;"
            : "+f"(d[0]), "+f"(d[1]), "+f"(d[2]), "+f"(d[3]), "+f"(d[4]), "+f"(d[5]), "+f"(d[6]), "+f"(d[7]),
              "+f"(d[8]), "+f"(d[9]), "+f"(d[10]), "+f"(d[11]), "+f"(d[12]), "+f"(d[13]), "+f"(d[14]), "+f"(d[15]),
              "+f"(d[16]), "+f"(d[17]), "+f"(d[18]), "+f"(d[19]), "+f"(d[20]), "+f"(d[21]), "+f"(d[22]), "+f"(d[23]),
              "+f"(d[24]), "+f"(d[25]), "+f"(d[26]), "+f"(d[27]), "+f"(d[28]), "+f"(d[29]), "+f"(d[30]), "+f"(d[31])
            : "l"(da), "l"(db));
    } else {
        asm volatile("wgmma.mma_async.sync.aligned.m64n64k16.f32.bf16.bf16 "
            "{%0, %1, %2, %3, %4, %5, %6, %7, %8, %9, %10, %11, %12, %13, %14, %15, %16, %17, %18, %19, %20, %21, %22, %23, %24, %25, %26, %27, %28, %29, %30, %31}, "
            "%32, %33, 0, 1, 1, 0, 1;"
            : "=f"(d[0]), "=f"(d[1]), "=f"(d[2]), "=f"(d[3]), "=f"(d[4]), "=f"(d[5]), "=f"(d[6]), "=f"(d[7]),
              "=f"(d[8]), "=f"(d[9]), "=f"(d[10]), "=f"(d[11]), "=f"(d[12]), "=f"(d[13]), "=f"(d[14]), "=f"(d[15]),
              "=f"(d[16]), "=f"(d[17]), "=f"(d[18]), "=f"(d[19]), "=f"(d[20]), "=f"(d[21]), "=f"(d[22]), "=f"(d[23]),
              "=f"(d[24]), "=f"(d[25]), "=f"(d[26]), "=f"(d[27]), "=f"(d[28]), "=f"(d[29]), "=f"(d[30]), "=f"(d[31])
            : "l"(da), "l"(db));
    }
}
template <bool ACC>
__device__ __forceinline__ void wgmma_ss_n128(float* d, uint64_t da, uint64_t db) {
    if constexpr (ACC) {
        asm volatile("wgmma.mma_async.sync.aligned.m64n128k16.f32.bf16.bf16 "
            "{%0, %1, %2, %3, %4, %5, %6, %7, %8, %9, %10, %11, %12, %13, %14, %15, %16, %17, %18, %19, %20, %21, %22, %23, %24, %25, %26, %27, %28, %29, %30, %31, %32, %33, %34, %35, %36, %37, %38, %39, %40, %41, %42, %43, %44, %45, %46, %47, %48, %49, %50, %51, %52, %53, %54, %55, %56, %57, %58, %59, %60, %61, %62, %63}, "
            "%64, %65, 1, 1, 1, 0, 1;"
            : "+f"(d[0]), "+f"(d[1]), "+f"(d[2]), "+f"(d[3]), "+f"(d[4]), "+f"(d[5]), "+f"(d[6]), "+f"(d[7]),
              "+f"(d[8]), "+f"(d[9]), "+f"(d[10]), "+f"(d[11]), "+f"(d[12]), "+f"(d[13]), "+f"(d[14]), "+f"(d[15]),
              "+f"(d[16]), "+f"(d[17]), "+f"(d[18]), "+f"(d[19]), "+f"(d[20]), "+f"(d[21]), "+f"(d[22]), "+f"(d[23]),
              "+f"(d[24]), "+f"(d[25]), "+f"(d[26]), "+f"(d[27]), "+f"(d[28]), "+f"(d[29]), "+f"(d[30]), "+f"(d[31]),
              "+f"(d[32]), "+f"(d[33]), "+f"(d[34]), "+f"(d[35]), "+f"(d[36]), "+f"(d[37]), "+f"(d[38]), "+f"(d[39]),
              "+f"(d[40]), "+f"(d[41]), "+f"(d[42]), "+f"(d[43]), "+f"(d[44]), "+f"(d[45]), "+f"(d[46]), "+f"(d[47]),
              "+f"(d[48]), "+f"(d[49]), "+f"(d[50]), "+f"(d[51]), "+f"(d[52]), "+f"(d[53]), "+f"(d[54]), "+f"(d[55]),
              "+f"(d[56]), "+f"(d[57]), "+f"(d[58]), "+f"(d[59]), "+f"(d[60]), "+f"(d[61]), "+f"(d[62]), "+f"(d[63])
            : "l"(da), "l"(db));
    } else {
        asm volatile("wgmma.mma_async.sync.aligned.m64n128k16.f32.bf16.bf16 "
            "{%0, %1, %2, %3, %4, %5, %6, %7, %8, %9, %10, %11, %12, %13, %14, %15, %16, %17, %18, %19, %20, %21, %22, %23, %24, %25, %26, %27, %28, %29, %30, %31, %32, %33, %34, %35, %36, %37, %38, %39, %40, %41, %42, %43, %44, %45, %46, %47, %48, %49, %50, %51, %52, %53, %54, %55, %56, %57, %58, %59, %60, %61, %62, %63}, "
            "%64, %65, 0, 1, 1, 0, 1;"
            : "=f"(d[0]), "=f"(d[1]), "=f"(d[2]), "=f"(d[3]), "=f"(d[4]), "=f"(d[5]), "=f"(d[6]), "=f"(d[7]),
              "=f"(d[8]), "=f"(d[9]), "=f"(d[10]), "=f"(d[11]), "=f"(d[12]), "=f"(d[13]), "=f"(d[14]), "=f"(d[15]),
              "=f"(d[16]), "=f"(d[17]), "=f"(d[18]), "=f"(d[19]), "=f"(d[20]), "=f"(d[21]), "=f"(d[22]), "=f"(d[23]),
              "=f"(d[24]), "=f"(d[25]), "=f"(d[26]), "=f"(d[27]), "=f"(d[28]), "=f"(d[29]), "=f"(d[30]), "=f"(d[31]),
              "=f"(d[32]), "=f"(d[33]), "=f"(d[34]), "=f"(d[35]), "=f"(d[36]), "=f"(d[37]), "=f"(d[38]), "=f"(d[39]),
              "=f"(d[40]), "=f"(d[41]), "=f"(d[42]), "=f"(d[43]), "=f"(d[44]), "=f"(d[45]), "=f"(d[46]), "=f"(d[47]),
              "=f"(d[48]), "=f"(d[49]), "=f"(d[50]), "=f"(d[51]), "=f"(d[52]), "=f"(d[53]), "=f"(d[54]), "=f"(d[55]),
              "=f"(d[56]), "=f"(d[57]), "=f"(d[58]), "=f"(d[59]), "=f"(d[60]), "=f"(d[61]), "=f"(d[62]), "=f"(d[63])
            : "l"(da), "l"(db));
    }
}

__device__ __forceinline__ void glu_tile(const float* gacc, const float* uacc, uint32_t cs1a, float nm0, float nm1,
                                         float k0, float k1, float v0, float v1, uint32_t& o0, uint32_t& o1) {
    float2 c1 = lds64(cs1a), c3 = lds64(cs1a + 896);
    float tg0 = fmaf(nm0, c1.x, gacc[0]), tg1 = fmaf(nm0, c1.y, gacc[1]), tg2 = fmaf(nm1, c1.x, gacc[2]), tg3 = fmaf(nm1, c1.y, gacc[3]);
    float tu0 = fmaf(nm0, c3.x, uacc[0]), tu1 = fmaf(nm0, c3.y, uacc[1]), tu2 = fmaf(nm1, c3.x, uacc[2]), tu3 = fmaf(nm1, c3.y, uacc[3]);
    float r0 = rcp(fmaf(ex2(tg0 * k0), v0, v0)), r1 = rcp(fmaf(ex2(tg1 * k0), v0, v0));
    float r2 = rcp(fmaf(ex2(tg2 * k1), v1, v1)), r3 = rcp(fmaf(ex2(tg3 * k1), v1, v1));
    o0 = pack2(tg0 * tu0 * r0, tg1 * tu1 * r1);
    o1 = pack2(tg2 * tu2 * r2, tg3 * tu3 * r3);
}

__device__ __forceinline__ float quad_sum(float v) {
    v += __shfl_xor_sync(0xffffffffu, v, 1);
    return v + __shfl_xor_sync(0xffffffffu, v, 2);
}

__device__ __forceinline__ void put_stats(uint4* row, int c, float s0, float q0, float s1, float q1, unsigned ep) {
    s0 = quad_sum(s0); q0 = quad_sum(q0); s1 = quad_sum(s1); q1 = quad_sum(q1);
    if (c < 2) stbox(row + 8 * c, __float_as_uint(c ? s1 : s0), __float_as_uint(c ? q1 : q0), ep, 0);
}
__device__ __forceinline__ void ld_stats(uint32_t (&st)[4][4], const uint4* sp) {
#pragma unroll
    for (int k = 0; k < 4; k++) ldbox(st[k], sp + (k & 1) * 128 + (k >> 1) * 8);
}
__device__ __forceinline__ void get_stats(uint32_t (&st)[4][4], const uint4* sp, unsigned ep, float& m0, float& m1, float& v0, float& v1) {
    int n = 0;
    while (true) {
        const bool bad = ((st[0][2] ^ ep) | (st[1][2] ^ ep) | (st[2][2] ^ ep) | (st[3][2] ^ ep) | st[0][3] | st[1][3] | st[2][3] | st[3][3]) != 0;
        if (!__any_sync(0xffffffffu, bad) || ++n > SPIN_LIMIT) break;
        ld_stats(st, sp);
    }
    const float s0 = quad_sum(__uint_as_float(st[0][0]) + __uint_as_float(st[1][0])), q0 = quad_sum(__uint_as_float(st[0][1]) + __uint_as_float(st[1][1]));
    const float s1 = quad_sum(__uint_as_float(st[2][0]) + __uint_as_float(st[3][0])), q1 = quad_sum(__uint_as_float(st[2][1]) + __uint_as_float(st[3][1]));
    m0 = s0 * (1.f / 512); m1 = s1 * (1.f / 512);
    v0 = fmaxf(q0 * (1.f / 512) - m0 * m0, 0.f) + 1e-5f; v1 = fmaxf(q1 * (1.f / 512) - m1 * m1, 0.f) + 1e-5f;
}

template <int STRIDE, bool INIT>
__device__ __forceinline__ void colsum8(float (&s)[8], const uint4* q) {
    uint4 v[8];
#pragma unroll
    for (int i = 0; i < 8; i++) v[i] = __ldg(q + i * STRIDE);
#pragma unroll
    for (int i = 0; i < 8; i++) {
        if (INIT && i == 0) {
            s[0] = blo(v[i].x); s[1] = bhi(v[i].x); s[2] = blo(v[i].y); s[3] = bhi(v[i].y);
            s[4] = blo(v[i].z); s[5] = bhi(v[i].z); s[6] = blo(v[i].w); s[7] = bhi(v[i].w);
        } else {
            s[0] += blo(v[i].x); s[1] += bhi(v[i].x); s[2] += blo(v[i].y); s[3] += bhi(v[i].y);
            s[4] += blo(v[i].z); s[5] += bhi(v[i].z); s[6] += blo(v[i].w); s[7] += bhi(v[i].w);
        }
    }
}
template <int STRIDE>
__device__ __forceinline__ void gather8(float (&t)[4], const uint4* q, uint32_t tag) {
    uint32_t v[8][4];
    int n = 0;
    uint32_t bad;
    do {
        bad = 0;
#pragma unroll
        for (int i = 0; i < 8; i++) ldbox(v[i], q + i * STRIDE);
#pragma unroll
        for (int i = 0; i < 8; i++) bad |= v[i][0] ^ tag;
    } while ((bad & 3u) && ++n < SPIN_LIMIT);
#pragma unroll
    for (int i = 0; i < 8; i++)
#pragma unroll
        for (int k = 0; k < 4; k++) t[k] += __uint_as_float(v[i][k]);
}
__device__ __forceinline__ int kc_at(int j, int d) { return d == 0 ? j : d - 1 + (d - 1 >= j); }
__device__ __forceinline__ void add_frag4(float* sum, const uint32_t (&in)[4]) {
#pragma unroll
    for (int i = 0; i < 4; i++) { sum[2 * i] += blo(in[i]); sum[2 * i + 1] += bhi(in[i]); }
}
__device__ __forceinline__ void set_frag(float* sum, const uint32_t (&in)[4]) {
#pragma unroll
    for (int i = 0; i < 4; i++) { sum[2 * i] = blo(in[i]); sum[2 * i + 1] = bhi(in[i]); }
}
__device__ __forceinline__ void add_frag(float (&sum)[32], const uint32_t (&in)[4][4]) {
#pragma unroll
    for (int k = 0; k < 4; k++) add_frag4(sum + 8 * k, in[k]);
}
__device__ __forceinline__ void pack_frag(uint32_t (&o)[4][4], const float (&a)[32]) {
#pragma unroll
    for (int i = 0; i < 8; i++) { o[i >> 1][(i & 1) * 2] = pack2(a[4 * i], a[4 * i + 1]); o[i >> 1][(i & 1) * 2 + 1] = pack2(a[4 * i + 2], a[4 * i + 3]); }
}
__host__ __device__ constexpr uint32_t dkeep(int i) { return i == 0 ? 192 : i == 1 ? 128 : i == 2 ? 152 : i == 3 ? 16 : i == 4 ? 176 : i == 11 ? 192 : 40 + (i - 5) * 16; }
__host__ __device__ constexpr uint32_t dsend(int i) { return i == 10 ? 216 : dkeep(i) + (i < 4 ? 12 : 8); }

__global__ void __launch_bounds__(384, 1) fused_block_kernel(const __grid_constant__ Params P) {
    extern __shared__ __align__(1024) unsigned char smem_raw[];
    if ((uint32_t)__cvta_generic_to_shared(smem_raw) != SB) return;
    constexpr uint32_t bar = SB + SM_BAR;
    const int tid = threadIdx.x, lane = tid & 31;
    if (TMPF && tid >= 288 && tid < 297) asm volatile("prefetch.tensormap [%0];" ::"l"(&P.tmX + (tid - 288)) : "memory");
    int cta = blockIdx.x;
    if (P.by_smid) {
        unsigned sm;
        asm("mov.u32 %0, %%smid;" : "=r"(sm));
        if (sm - 120u < 4u) {
            const unsigned ep = *(volatile unsigned*)&g_epoch[128 + sm - 120] + 1;
            if (tid < 128) {
                uint32_t v[4];
                int n = 0;
                do ldbox(v, g_csq + tid * 48); while (((v[0] ^ ((ep & 1) ? 1u : 2u)) & 3u) && ++n < SPIN_LIMIT);
            }
            __syncthreads();
            if (tid == 0) *(volatile unsigned*)&g_epoch[128 + sm - 120] = ep;
            return;
        }
        const int q = sm < 64 ? (sm & 15) >> 1 : sm < 120 ? 1 + ((sm - 64) % 14 >> 1) : 0;
        const int rk = sm < 64 ? (sm >> 4) * 2 + (sm & 1) : sm < 120 ? 8 + (sm - 64) / 14 * 2 + (sm & 1) : sm - 116;
        cta = ((q >> 1) * 4 + (rk >> 2)) * 8 + (rk & 3) * 2 + (q & 1);
    }
    cta = __shfl_sync(0xffffffffu, cta, 0);
    const int g = cta >> 3, j = cta & 7;
    const int warp = __shfl_sync(0xffffffffu, tid >> 5, 0);
    const int qd = j & 1, offA64 = qd ? 32 : 128, offA32 = qd ? 0 : 192, offB = qd ? 96 : 64, offC = qd ? 160 : 0;
    PROF_INIT;
    PROF_START;

#define PT(i)
    PT(0);
    if (warp >= 8) {
        asm volatile("setmaxnreg.dec.sync.aligned.u32 56;");
        PT(1);
        if (warp == 8) {
            auto init_bars = [&](bool early) {
                if (lane == 0) {
#pragma unroll
                    for (int i = 0; i < B_N; i++) {
                        const bool e8 = (i >= B_WE && i < B_OF) || (i >= B_GE && i < B_DF) || i == B_DE || i == B_HX || i == B_WD;
                        const bool first = (i >= B_XF && i < B_XF + LOOKAHEAD) || (i >= B_WF && i < B_WF + LOOKAHEAD);
                        if (first == early) mbar_init(bar + i * 8, e8 ? 8 : i >= B_CS1 ? 3 : 1);
                    }
                    asm volatile("fence.proxy.async.shared::cta;" ::: "memory");
                }
                __syncwarp();
            };
            init_bars(true);
            PT(2);
            const int f0 = j * 224;
#pragma unroll 1
            for (int d = 0; d < 8; d++) {
                const int s = d & 3;
                if (d == LOOKAHEAD) {
                    PT(3);
                    init_bars(false);
                    asm volatile("bar.arrive 0, 384;" ::: "memory");
                    PT(4);
                }
                if (d >= LOOKAHEAD) mbar_wait(bar + (B_WF + ((d - LOOKAHEAD) & 3)) * 8, (d - LOOKAHEAD) >> 2);
#pragma unroll 1
                for (int e = d < LOOKAHEAD ? d : d == LOOKAHEAD ? d : d + XAHEAD; e <= (d < LOOKAHEAD ? d : d + XAHEAD) && e < 8; e++) {
                    mbar_expect_e(bar + (B_XF + e) * 8, 16384);
                    tma3d_e(SB + SM_ACT + e * 16384, &P.tmX, e * 64, g * 64, bar + (B_XF + e) * 8);
                }
                if (d >= 4) mbar_wait(bar + (B_WE + s) * 8, 0);
                mbar_expect_e(bar + (B_WF + s) * 8, 24576);
                tma3d_e(SB + SM_RING + s * 24576, &P.tmQKV, j * 64, d * 64, bar + (B_WF + s) * 8);
                PROFD(32 + d);
            }
            mbar_wait(bar + (B_WE + 3) * 8, 1);
            mbar_expect_e(bar + B_OF * 8, 65536);
            tma2d_e(SB + SM_ACT + 65536, &P.tmWO, j * 64, 0, bar + B_OF * 8);
            tma2d_e(SB + SM_ACT + 98304, &P.tmWO, j * 64, 256, bar + B_OF * 8);
#pragma unroll 1
            for (int d = 0; d < 8; d++) {
                const uint32_t dst = SB + SM_RING + (d & 3) * 24576, fb = bar + (B_WF + (d & 3)) * 8;
                const int row = kc_at(j, d) * 64;
                if (d >= 4) mbar_wait(bar + (B_WE + (d & 3)) * 8, 0);
                else mbar_wait(d == 0 ? bar + B_OF * 8 : fb - 8, 0);
                mbar_expect_e(fb, 24576);
                tma2d_e(dst, &P.tmW1, f0 + offA64, row, fb);
                tma2d_e(dst + 8192, &P.tmW3, f0 + offA64, row, fb);
                tma2d_e(dst + 16384, &P.tmW1h, f0 + offA32, row, fb);
                tma2d_e(dst + 20480, &P.tmW3h, f0 + offA32, row, fb);
            }
            int sl = 0;
#pragma unroll 1
            for (int n = 0; n < 16; n++) {
                const uint32_t dst = SB + SM_RING + sl * 16384, fb = bar + (B_GF + sl) * 8;
                const int row = kc_at(j, n & 7) * 64, col = f0 + (n < 8 ? offB : offC);
                mbar_wait(bar + (n < 6 ? B_WE + ((0x332110 >> (4 * n)) & 3) : B_GE + sl) * 8, n < 6 || n >= 12);
                mbar_expect_e(fb, 16384);
                tma2d_e(dst, &P.tmW1, col, row, fb);
                tma2d_e(dst + 8192, &P.tmW3, col, row, fb);
                if (++sl == 6) sl = 0;
            }
#pragma unroll 1
            for (int i = 0; i < 12; i++) {
                const uint32_t fb = bar + (B_DF + i) * 8;
                const int src = 2 * (i < 8 ? i & 3 : kc_at(j >> 1, i - 8)) + qd;
                const int row = src * 224 + (i < 4 ? (qd ? 0 : 128) : i < 8 ? offB : offC);
                if (i < 3) mbar_wait(bar + (B_GE + ((0x315 >> (4 * i)) & 7)) * 8, i == 0);
                if (i == 11) mbar_wait(bar + B_DE * 8, 0);
                if (i >= 2 + DLA) mbar_wait(fb - 8 * DLA, 0);
                const CUtensorMap* tm = i < 4 ? &P.tmW2a : &P.tmW2;
                mbar_expect_e(fb, i < 4 ? 24576 : 16384);
                tma2d_e(SB + dkeep(i) * 1024, tm, j * 64, row, fb);
                tma2d_e(SB + dsend(i) * 1024, tm, (j ^ 1) * 64, row, fb);
            }
            PROF_END;
        } else {
            const int hw = warp - 9, ht = tid - 288;
            unsigned ep;
            asm volatile("ld.relaxed.gpu.global.u32 %0, [%1];" : "=r"(ep) : "l"(g_epoch + cta));
            asm volatile("bar.sync 0, 384;" ::: "memory");
            ep += 1;
            const uint32_t tag = (ep & 1) ? 1u : 2u;
            {
                float s[8];
                const uint4* q = reinterpret_cast<const uint4*>(P.wqkv + (g * 32 + (lane >> 3)) * 1536 + hw * 512 + j * 64) + (lane & 7);
                colsum8<4 * 192, true>(s, q);
                const bool b4 = lane & 16;
                float t[4];
#pragma unroll
                for (int i = 0; i < 4; i++) {
                    t[i] = (b4 ? s[i + 4] : s[i]) + __shfl_xor_sync(0xffffffffu, b4 ? s[i] : s[i + 4], 16);
                    t[i] += __shfl_xor_sync(0xffffffffu, t[i], 8);
                }
                if (!(lane & 8))
                    stbox(g_csq + (cta * 3 + hw) * 16 + (lane & 7) * 2 + (lane >> 4), (__float_as_uint(t[0]) & ~3u) | tag, __float_as_uint(t[1]), __float_as_uint(t[2]), __float_as_uint(t[3]));
            }
            PROF(42);
            if (hw == 2) {
                const uint32_t fr = SB + SM_ACT + j * 2048 + (lane & 15) * 128 + (((lane >> 4) ^ (lane & 7)) << 4);
                float s0 = 0.f, q0 = 0.f, s1 = 0.f, q1 = 0.f;
#pragma unroll 1
                for (int d = 0; d < 8; d++) {
                    uint32_t a[4][4];
                    mbar_wait(bar + (B_XF + d) * 8, 0);
#pragma unroll
                    for (int k = 0; k < 4; k++) ldsm4(a[k], (fr ^ (k * 32)) + d * 16384);
#pragma unroll
                    for (int k = 0; k < 4; k++)
#pragma unroll
                        for (int h = 0; h < 2; h++) {
                            const float x0 = blo(a[k][2 * h]), x1 = bhi(a[k][2 * h]), y0 = blo(a[k][2 * h + 1]), y1 = bhi(a[k][2 * h + 1]);
                            s0 += x0 + x1; q0 = fmaf(x0, x0, q0); q0 = fmaf(x1, x1, q0);
                            s1 += y0 + y1; q1 = fmaf(y0, y0, q1); q1 = fmaf(y1, y1, q1);
                        }
                }
                s0 = quad_sum(s0); q0 = quad_sum(q0); s1 = quad_sum(s1); q1 = quad_sum(q1);
                const float m = ((lane & 1) ? s1 : s0) * (1.f / 512), q = ((lane & 1) ? q1 : q0) * (1.f / 512);
                if (!(lane & 2)) stbox(g_stat + cta * 16 + (lane >> 2) + (lane & 1) * 8, __float_as_uint(m), __float_as_uint(rsq(fmaxf(q - m * m, 0.f) + 1e-5f)), ep, 0);
            }
            PROF(41);
            mbar_wait(bar + (B_XF + GQ_AT) * 8, 0);
            PROF(43);
            {
                float t[4] = {0.f, 0.f, 0.f, 0.f};
                gather8<24 * 16>(t, g_csq + (((lane >> 4) * 64 + j) * 3 + hw) * 16 + (lane & 15), tag);
#pragma unroll
                for (int i = 0; i < 4; i++) t[i] += __shfl_xor_sync(0xffffffffu, t[i], 16);
                if (lane < 16) asm volatile("st.shared.v4.f32 [%0], {%1,%2,%3,%4};" ::"r"(SB + SM_CSQ + hw * 256 + lane * 16), "f"(t[0]), "f"(t[1]), "f"(t[2]), "f"(t[3]) : "memory");
            }
            __syncwarp();
            if (lane == 0) mbar_arrive(bar + B_CS1 * 8);
            PROF(44);
            if (hw < 2 && lane < 28) {
                float s[8];
                const uint4* q = reinterpret_cast<const uint4*>((hw ? P.w3 : P.w1) + g * 32 * 1792 + j * 224) + lane;
#pragma unroll
                for (int i = 0; i < 8; i++) s[i] = 0.f;
#pragma unroll 1
                for (int b = 0; b < 4; b++) colsum8<224, false>(s, q + b * 8 * 224);
                uint4* dst = g_cs13 + (cta * 2 + hw) * 56 + lane * 2;
                stbox(dst, (__float_as_uint(s[0]) & ~3u) | tag, __float_as_uint(s[1]), __float_as_uint(s[2]), __float_as_uint(s[3]));
                stbox(dst + 1, (__float_as_uint(s[4]) & ~3u) | tag, __float_as_uint(s[5]), __float_as_uint(s[6]), __float_as_uint(s[7]));
            }
            PROF(46);
            mbar_wait(bar + B_HX * 8, 0);
#pragma unroll 1
            for (int v = ht; v < 112; v += 96) {
                float t[4] = {0.f, 0.f, 0.f, 0.f};
#pragma unroll 1
                for (int h = 0; h < 2; h++) gather8<16 * 56>(t, g_cs13 + (h * 64 + j) * 112 + v, tag);
                asm volatile("st.shared.v4.f32 [%0], {%1,%2,%3,%4};" ::"r"(SB + SM_CS13 + v * 16), "f"(t[0]), "f"(t[1]), "f"(t[2]), "f"(t[3]) : "memory");
            }
            __syncwarp();
            if (lane == 0) mbar_arrive(bar + B_CS2 * 8);
            PROF(47);
        }
    } else {
        asm volatile("setmaxnreg.inc.sync.aligned.u32 224;");
        unsigned ep;
        asm volatile("ld.relaxed.gpu.global.u32 %0, [%1];" : "=r"(ep) : "l"(g_epoch + cta));
        asm volatile("bar.sync 0, 384;" ::: "memory");
        const uint32_t id0 = cta | tid << 8;
#define PHASE                                                                                                                        \
    uint32_t id_ = id0;                                                                                                              \
    asm volatile("" : "+r"(id_));                                                                                                    \
    const uint32_t idu_ = __shfl_sync(0xffffffffu, id_, 0);                                                    \
    [[maybe_unused]] const int cta = idu_ & 127, g = cta >> 3, j = cta & 7, gb = cta & ~7, qd = j & 1;                               \
    [[maybe_unused]] const int tid = id_ >> 8, lane = tid & 31, warp = idu_ >> 13, p = warp >> 2, w = warp & 3, r = lane >> 2, c = lane & 3; \
    [[maybe_unused]] const int boxoff = warp * 128 + lane;                                                       \
    [[maybe_unused]] const int offA64 = qd ? 32 : 128, offA32 = qd ? 0 : 192, offB = qd ? 96 : 64, offC = qd ? 160 : 0;              \
                              \
    [[maybe_unused]] const uint32_t fragA = SB + SM_ACT + p * 8192 + (w * 16 + (lane & 15)) * 128 + (((lane >> 4) ^ (lane & 7)) << 4); \
    [[maybe_unused]] const uint32_t priv = SB + SM_ACT + p * 8192 + w * 2048 + lane * 16;         \
    [[maybe_unused]] const uint32_t csb = SB + SM_CS13 + c * 8;                                                                      \
    [[maybe_unused]] uint4* const my_p = g_pbox + (cta * 8 + warp) * 448 + lane;                                                     \
    [[maybe_unused]] const uint4* const pq = g_pbox + ((gb + qd) * 8 + warp) * 448 + lane
#define FRAG(slot, ks) ((fragA ^ ((ks) * 32)) + (slot) * 16384)

        uint32_t res[4][4];
        uint32_t own[4][4];
        uint32_t tag;
        {
            PHASE;
            float aq[32], akv[64];
            const uint64_t dR = P.dB128[0] + (SM_RING >> 4);
            const uint64_t dA = P.dA[0] + (SM_ACT >> 4) + p * 512;
            auto chunk = [&](int d, bool first, bool withQ) {
                const uint64_t a = dA + d * 1024, b = dR + (d & 3) * 1536;
                mbar_wait(bar + (B_XF + d) * 8, 0);
                mbar_wait(bar + (B_WF + (d & 3)) * 8, d >> 2);
                PROFD(32 + d);
                wg_fence();
#pragma unroll
                for (int k = 0; k < 4; k++) {
                    if (first && k == 0) { wgmma_ss_n128<false>(akv, a, b + 512); wgmma_ss_n64<false>(aq, a, b); }
                    else {
                        wgmma_ss_n128<true>(akv, a + k * 2, b + 512 + k * 128);
                        if (withQ) wgmma_ss_n64<true>(aq, a + k * 2, b + k * 128);
                    }
                }
                wg_commit();
                if (!first && withQ) {
                    wg_wait<1>();
                    if (lane == 0) mbar_arrive(bar + (B_WE + ((d - 1) & 3)) * 8);
                }
            };
            auto clear2 = [&](uint4* z) { if (CLR) { stbox(z, 0, 0, 0, 0); stbox(z + 32, 0, 0, 0, 0); } };
            uint4* const my_halo = g_halo + (cta * 2 + p) * 128 + lane;
            chunk(0, true, true);
            if (w == 3) { clear2(my_halo); clear2(my_halo + 64); }
#pragma unroll 1
            for (int d = 1; d < 8 - QDEF; d++) {
                chunk(d, false, true);
                if (d < 5) clear2((d < 3 ? g_obox : g_hbox) + ((d - 1) & 1) * 64 + cta * 1024 + boxoff);
            }
            uint32_t st[2][4];
            const uint4* const sp = g_stat + (gb + warp) * 16 + r;
            if (QDEF == 3) chunk(5, false, false);
            chunk(6, false, false);
            ldbox(st[0], sp); ldbox(st[1], sp + 8);
            chunk(7, false, false);
#pragma unroll
            for (int k = 0; k < 4; k++) ldsm4(res[k], FRAG(j, k));
            ep += 1;
            tag = (ep & 1) ? 1u : 0x10000u;
            for (int n = 0; __any_sync(0xffffffffu, ((st[0][2] ^ ep) | (st[1][2] ^ ep) | st[0][3] | st[1][3]) != 0) && n < SPIN_LIMIT; n++) { ldbox(st[0], sp); ldbox(st[1], sp + 8); }
            const float m0 = __uint_as_float(st[0][0]), m1 = __uint_as_float(st[1][0]), rs0 = __uint_as_float(st[0][1]), rs1 = __uint_as_float(st[1][1]);
            const float n0 = -m0 * rs0, n1 = -m1 * rs1;
            auto mma_q = [&](int d) {
                wg_fence();
#pragma unroll
                for (int k = 0; k < 4; k++) wgmma_ss_n64<true>(aq, dA + d * 1024 + k * 2, dR + (d & 3) * 1536 + k * 128);
                wg_commit();
            };
            mbar_wait(bar + B_CS1 * 8, 0);
            mma_q(8 - QDEF);
            wg_wait<1>();
            reg_fence<64>(akv);
            PROF(3);
            uint32_t K1[8], K2[8], V1[8], V2[8];
#pragma unroll
            for (int i = 0; i < 16; i++) {
                const float* a = akv + 4 * i;
                const float2 cs = lds64(SB + SM_CSQ + 256 + i * 32 + c * 8);
                const uint32_t hi = pack2(fmaf(a[2], rs1, n1 * cs.x), fmaf(a[3], rs1, n1 * cs.y));
                if (i < 8) K2[i] = hi; else V2[i - 8] = movm(hi);
                if (i == 3 && QDEF == 3) mma_q(6);
            }
            if (w == 3) {
#pragma unroll
                for (int h = 0; h < 4; h++) stbox(my_halo + h * 32, (K2[2 * h] & ~TAGM) | tag, K2[2 * h + 1], V2[2 * h], V2[2 * h + 1]);
            } else {
#pragma unroll
                for (int h = 0; h < 4; h++)
                    asm volatile("st.shared.v4.u32 [%0], {%1,%2,%3,%4};" ::"r"(priv + h * 512), "r"(K2[2 * h]), "r"(K2[2 * h + 1]), "r"(V2[2 * h]), "r"(V2[2 * h + 1]) : "memory");
            }
            __syncwarp();
            PROF(2);
            mma_q(7);
#pragma unroll
            for (int i = 0; i < 16; i++) {
                const float* a = akv + 4 * i;
                const float2 cs = lds64(SB + SM_CSQ + 256 + i * 32 + c * 8);
                const uint32_t lo = pack2(fmaf(a[0], rs0, n0 * cs.x), fmaf(a[1], rs0, n0 * cs.y));
                if (i < 8) K1[i] = lo; else V1[i - 8] = movm(lo);
            }
            uint32_t prev[4][4];
            if (w == 0 && g > 0) ldgroup(prev, my_halo - 8 * 2 * 128);
            wg_wait<0>();
            reg_fence<32>(aq);
            if (lane == 0) {
#pragma unroll
                for (int i = 3 - QDEF; i < 4; i++) mbar_arrive(bar + (B_WE + i) * 8);
            }
            PROF(4);
            const float qs = 0.25f * 1.4426950408889634f;
            const float rq0 = rs0 * qs, rq1 = rs1 * qs, nq0 = n0 * qs, nq1 = n1 * qs;
            uint32_t Q[4][4];
#pragma unroll
            for (int i = 0; i < 8; i++) {
                const float2 cs = lds64(SB + SM_CSQ + i * 32 + c * 8);
                Q[i >> 1][(i & 1) * 2] = pack2(fmaf(aq[4 * i], rq0, nq0 * cs.x), fmaf(aq[4 * i + 1], rq0, nq0 * cs.y));
                Q[i >> 1][(i & 1) * 2 + 1] = pack2(fmaf(aq[4 * i + 2], rq1, nq1 * cs.x), fmaf(aq[4 * i + 3], rq1, nq1 * cs.y));
            }
            float S1[4][4], S2[4][4];
#pragma unroll
            for (int h = 0; h < 4; h++) {
#pragma unroll
                for (int i = 0; i < 4; i++) { S1[h][i] = 0.f; S2[h][i] = 0.f; }
                mma16(S1[h], Q[h][0], Q[h][1], Q[h][2], Q[h][3], K1[2 * h], K1[2 * h + 1]);
                mma16(S2[h], Q[h][0], Q[h][1], Q[h][2], Q[h][3], K2[2 * h], K2[2 * h + 1]);
            }
            asm volatile("bar.sync %0, 128;" ::"r"(1 + p) : "memory");
            if (w == 0) {
                if (g > 0) chkgroup(prev, my_halo - 8 * 2 * 128, tag);
                else {
#pragma unroll
                    for (int h = 0; h < 4; h++) prev[h][0] = prev[h][1] = prev[h][2] = prev[h][3] = 0;
                }
            } else {
#pragma unroll
                for (int h = 0; h < 4; h++) lds128(prev[h], priv - 2048 + h * 512);
            }
            PROF(5);
            const bool up0 = 2 * c > r, up1 = 2 * c + 1 > r, first = (g == 0 && w == 0);
            const uint32_t M = (up0 ? 0xffffu : 0u) | (up1 ? 0xffff0000u : 0u);
            const float NEG = -1e9f * 1.4426950408889634f;
#pragma unroll
            for (int h = 0; h < 4; h++) {
                float S0[4] = {0.f, 0.f, 0.f, 0.f};
                mma16(S0, Q[h][0], Q[h][1], Q[h][2], Q[h][3], prev[h][0], prev[h][1]);
                const float a0 = up0 ? (first ? NEG : S0[0]) : S1[h][0], a1 = up1 ? (first ? NEG : S0[1]) : S1[h][1];
                const float b0 = up0 ? S1[h][2] : S2[h][2], b1 = up1 ? S1[h][3] : S2[h][3];
                float ma = fmaxf(a0, a1), mb = fmaxf(b0, b1);
                ma = fmaxf(ma, __shfl_xor_sync(0xffffffffu, ma, 1)); mb = fmaxf(mb, __shfl_xor_sync(0xffffffffu, mb, 1));
                ma = fmaxf(ma, __shfl_xor_sync(0xffffffffu, ma, 2)); mb = fmaxf(mb, __shfl_xor_sync(0xffffffffu, mb, 2));
                const float ea0 = ex2(a0 - ma), ea1 = ex2(a1 - ma), eb0 = ex2(b0 - mb), eb1 = ex2(b1 - mb);
                const float ia = rcp(quad_sum(ea0 + ea1)), ib = rcp(quad_sum(eb0 + eb1));
                const uint32_t P0 = pack2(ea0 * ia, ea1 * ia), P1 = pack2(eb0 * ib, eb1 * ib);
#pragma unroll
                for (int D = 0; D < 2; D++) {
                    float O[4] = {0.f, 0.f, 0.f, 0.f};
                    mma16(O, P0 & M, 0u, P0 & ~M, P1 & M, prev[h][2 + D], V1[2 * h + D]);
                    mma8(O, 0u, P1 & ~M, V2[2 * h + D]);
                    own[h][2 * D] = pack2(O[0], O[1]);
                    own[h][2 * D + 1] = pack2(O[2], O[3]);
                }
                stbox(g_obox + cta * 1024 + boxoff + h * 32, (own[h][0] & ~TAGM) | tag, own[h][1], own[h][2], own[h][3]);
            }
            PROF(6);
        }
#define SRC(box, d) ((box) + (gb + kc_at(j, d)) * 1024 + boxoff)
        {
            PHASE;
            float ao[32];
            uint32_t in[7][4][4];
            const uint64_t b = P.dB128[0] + ((SM_ACT + 65536) >> 4);
            asm volatile("bar.sync %0, 128;" ::"r"(1 + p) : "memory");
            PROF(60);
            mbar_wait(bar + B_OF * 8, 0);
            PROF(61);
            wg_fence();
            wgmma_rs_n64<false>(ao, own[0], b + j * 512);
#pragma unroll
            for (int k = 1; k < 4; k++) wgmma_rs_n64<true>(ao, own[k], b + j * 512 + k * 128);
            wg_commit();
            pollgroup(in[0], SRC(g_obox, 1), tag);
            PROF(7);
            auto cp_in = [&](int e) {
                const uint4* src = SRC(g_obox, e);
#pragma unroll
                for (int i = 0; i < 4; i++) asm volatile("cp.async.cg.shared.global [%0], [%1], 16;" ::"r"(priv + (e - 2) * 16384 + i * 512), "l"(src + i * 32) : "memory");
                asm volatile("cp.async.commit_group;" ::: "memory");
            };
            auto lds_in = [&](int e) {
#pragma unroll
                for (int i = 0; i < 4; i++) lds128(in[e - 1][i], priv + (e - 2) * 16384 + i * 512);
            };
            auto mma_o = [&](int d) {
                if (d > 1) chkgroup(in[d - 1], SRC(g_obox, d), tag);
                PROFD(62 + 2 * d);
                wg_fence();
#pragma unroll
                for (int k = 0; k < 4; k++) wgmma_rs_n64<true>(ao, in[d - 1][k], b + kc_at(j, d) * 512 + k * 128);
                wg_commit();
            };
            cp_in(2); cp_in(3);
            mma_o(1);
            cp_in(4); cp_in(5);
            cp_wait(2); lds_in(2); lds_in(3);
            ldgroup(in[5], SRC(g_obox, 6));
            ldgroup(in[6], SRC(g_obox, 7));
            mma_o(2); mma_o(3);
            cp_wait(0); lds_in(4); lds_in(5);
            mma_o(4); mma_o(5); mma_o(6); mma_o(7);
            wg_wait<0>();
            reg_fence<32>(ao);
            asm volatile("bar.arrive %0, 256;" ::"r"(3 + p) : "memory");
            if (lane == 0) mbar_arrive(bar + B_WD * 8);
            PROF(8);
            float s0 = 0.f, q0 = 0.f, s1 = 0.f, q1 = 0.f;
            add_frag(ao, res);
            pack_frag(own, ao);
            stgroup(g_hbox + cta * 1024 + boxoff, own, tag);
#pragma unroll
            for (int i = 0; i < 8; i++) {
                s0 += ao[4 * i] + ao[4 * i + 1]; q0 = fmaf(ao[4 * i], ao[4 * i], q0); q0 = fmaf(ao[4 * i + 1], ao[4 * i + 1], q0);
                s1 += ao[4 * i + 2] + ao[4 * i + 3]; q1 = fmaf(ao[4 * i + 2], ao[4 * i + 2], q1); q1 = fmaf(ao[4 * i + 3], ao[4 * i + 3], q1);
            }
            put_stats(g_stat + 2048 + cta * 128 + p * 64 + w * 16 + r, c, s0, q0, s1, q1, ep);
        }
        float aB[64];
        float nm0, nm1, k0, k1, v0, v1;
        uint32_t Pt[4];
#define GLU(acc, uoff, t, off, T0, F)                                                                                              \
    do {                                                                                                                           \
        glu_tile((acc) + 4 * (t), (acc) + (uoff) + 4 * (t), csb + (off) * 4 + 32 * (t), nm0, nm1, k0, k1, v0, v1, F[((t) & 1) * 2], F[((t) & 1) * 2 + 1]); \
        if ((t) & 1) stbox(my_p + ((T0) + ((t) >> 1)) * 32, (F[0] & ~TAGM) | tag, F[1], F[2], F[3]);                             \
    } while (0)
        {
            float aA[64], aH[32];
          {
            PHASE;
            uint32_t in[4][4][4];
            uint32_t st[4][4];
            const uint64_t dH = P.dB64 + ((SM_RING + 16384) >> 4), dR = P.dB128[1] + (SM_RING >> 4);
            __syncwarp();
#pragma unroll
            for (int k = 0; k < 4; k++) stsm4(FRAG(0, k), own[k]);
            mbar_wait(bar + B_WF * 8, 0);
            PROF(9);
            wg_fence();
#pragma unroll
            for (int k = 0; k < 4; k++) {
                if (k == 0) { wgmma_rs_n128<false>(aA, own[0], dR); wgmma_rs_n64<false>(aH, own[0], dH); }
                else { wgmma_rs_n128<true>(aA, own[k], dR + k * 128); wgmma_rs_n64<true>(aH, own[k], dH + k * 64); }
            }
            wg_commit();
            pollgroup(in[0], SRC(g_hbox, 1), tag);
            PROF(10);
            const uint4* const sp = g_stat + 2048 + (gb + 2 * c) * 128 + p * 64 + w * 16 + r;
#define HBUF(d) ((d) == 5 ? own : in[(d) < 5 ? (d) - 1 : (d) - 6])
#pragma unroll
            for (int d = 1; d < 8; d++) {
                uint32_t(&a)[4][4] = HBUF(d);
                mbar_wait(bar + (B_WF + (d & 3)) * 8, d >> 2);
                if (d > 1 && !(d & 1)) { chkgroup(a, SRC(g_hbox, d), tag); chkgroup(HBUF(d + 1), SRC(g_hbox, d + 1), tag); }
                if (d == 1) { ldgroup(HBUF(2), SRC(g_hbox, 2)); ldgroup(HBUF(3), SRC(g_hbox, 3)); }
                if (d == 2 || d == 4) ldgroup(HBUF(d + 2), SRC(g_hbox, d + 2));
                if (d == 6) ld_stats(st, sp);
                if (d == 4) asm volatile("bar.sync %0, 256;" ::"r"(4 - p) : "memory");
#pragma unroll
                for (int k = 0; k < 4; k++) stsm4(FRAG(d, k), a[k]);
                PROFD(48 + d);
                wg_fence();
#pragma unroll
                for (int k = 0; k < 4; k++) {
                    wgmma_rs_n128<true>(aA, a[k], dR + (d & 3) * 1536 + k * 128);
                    wgmma_rs_n64<true>(aH, a[k], dH + (d & 3) * 1536 + k * 64);
                }
                wg_commit();
                if (d == 2 || d == 4) ldgroup(HBUF(d + 3), SRC(g_hbox, d + 3));
                wg_wait<1>();
                if (lane == 0) {
                    mbar_arrive(bar + (B_WE + ((d - 1) & 3)) * 8);
                    if (d == 2) mbar_arrive(bar + B_HX * 8);
                }
            }
            get_stats(st, sp, ep, nm0, nm1, v0, v1);
            nm0 = -nm0; nm1 = -nm1;
            k0 = -1.4426950408889634f * rsq(v0); k1 = -1.4426950408889634f * rsq(v1);
            asm volatile("fence.proxy.async.shared::cta;" ::: "memory");
            asm volatile("bar.sync %0, 128;" ::"r"(1 + p) : "memory");
            PROF(11);
          }
            PHASE;
            const uint64_t dA = P.dA[0] + (SM_ACT >> 4) + p * 512, dRB = P.dB128[2] + (SM_RING >> 4);
#pragma unroll
            for (int d = 0; d < 8; d++) {
                mbar_wait(bar + (B_GF + d % 6) * 8, (d / 6) & 1);
                if (d == 0 && p == 1) asm volatile("bar.sync 5, 256;" ::: "memory");
                wg_fence();
#pragma unroll
                for (int k = 0; k < 4; k++) {
                    if (d == 0 && k == 0) wgmma_ss_n128<false>(aB, dA, dRB);
                    else wgmma_ss_n128<true>(aB, dA + d * 1024 + k * 2, dRB + (d % 6) * 1024 + k * 128);
                    if (d >= 1 && d < 7 && (k & 1)) {
                        wg_commit();
                        const int t = (d - 1) * 2 + (k >> 1);
                        if (t < 8) GLU(aA, 32, t, offA64, 0, Pt); else GLU(aH, 16, t - 8, offA32, 4, Pt);
                    }
                }
                if (d == 0 || d == 7) { wg_commit(); wg_wait<1>(); } else wg_wait<2>();
                if (lane == 0) mbar_arrive(bar + (d == 0 ? B_WE + 3 : B_GE + (d - 1) % 6) * 8);
                if (d == WGOFF && p == 0) asm volatile("bar.arrive 5, 256;" ::: "memory");
                if (d == 0) { reg_fence<64>(aA); reg_fence<32>(aH); mbar_wait(bar + B_CS2 * 8, 0); }
            }
        }
        float aK[32], aS[32];
        uint32_t G[2][8][4], C0[4][4], CX[4][4];
#define KSRC(i) (pq + ((i) < 24 ? (i) / 6 * 7168 + (i) % 6 * 32 : ((i) - 24) / 4 * 7168 + (6 + ((i) & 3)) * 32))
#define CSRC(i) (pq + kc_at(j >> 1, i) * 7168 + 320)
#define CBUF(i) ((i) == 0 ? C0 : (i) == 3 ? CX : reinterpret_cast<uint32_t(&)[4][4]>(G[1][((i) - 1) * 4]))
        {
            PHASE;
            float aC[64];
            const uint64_t dA = P.dA[1] + (SM_ACT >> 4) + p * 512, dR = P.dB128[3] + (SM_RING >> 4);
#pragma unroll
            for (int d = 0; d < 8; d++) {
                const int n = 8 + d;
                mbar_wait(bar + (B_GF + n % 6) * 8, (n / 6) & 1);
                wg_fence();
#pragma unroll
                for (int k = 0; k < 4; k++) {
                    if (d == 0 && k == 0) wgmma_ss_n128<false>(aC, dA, dR + (n % 6) * 1024);
                    else wgmma_ss_n128<true>(aC, dA + d * 1024 + k * 2, dR + (n % 6) * 1024 + k * 128);
                }
                wg_commit();
                wg_wait<1>();
                if (lane == 0) mbar_arrive(bar + (B_GE + (n - 1) % 6) * 8);
                if (d == 0) reg_fence<64>(aB);
                if (d < 4) stbox(g_part + (cta ^ 1) * 1024 + boxoff + d * 32, 0, 0, 0, 0);
                if (d == 5) {
#pragma unroll
                    for (int i = 0; i < 8; i++) ldbox(G[0][i], KSRC(i));
                }
                GLU(aB, 32, d, offB, 6, Pt);
            }
            const uint64_t dW = P.dB128[0], dW64 = dW + (qd ? 256 : 0), dW32 = dW + (qd ? 0 : 512);
#pragma unroll
            for (int u = 0; u < 20; u++) {
                const int bt = u >> 2, st = u < 12 ? u / 3 : 4 + (u - 12) / 2;
                if ((u < 12 ? u % 3 == 0 : (u & 1) == 0) || (u & 3) == 0) mbar_wait(bar + (B_DF + st) * 8, 0);
                if ((u & 3) == 0) {
                    int n = 0;
                    while (true) {
                        uint32_t bad = 0;
#pragma unroll
                        for (int i = 0; i < 8; i++) bad |= G[bt & 1][i][0] ^ tag;
                        if (!__any_sync(0xffffffffu, (bad & TAGM) != 0) || ++n > SPIN_LIMIT) break;
#pragma unroll
                        for (int i = 0; i < 8; i++) ldbox(G[bt & 1][i], KSRC(bt * 8 + i));
                    }
                }
                wg_fence();
#pragma unroll
                for (int k = 0; k < 2; k++) {
                    const uint32_t(&a)[4] = G[bt & 1][(u & 3) * 2 + k];
                    const uint64_t b = u >= 12 ? dW + ((u & 1) * 2 + k) * 128 : u % 3 < 2 ? dW64 + (u % 3 * 2 + k) * 128 : dW32 + k * 128;
                    if (u == 0 && k == 0) { wgmma_rs_n64<false>(aS, a, b + dsend(st) * 64); wgmma_rs_n64<false>(aK, a, b + dkeep(st) * 64); }
                    else { wgmma_rs_n64<true>(aS, a, b + dsend(st) * 64); wgmma_rs_n64<true>(aK, a, b + dkeep(st) * 64); }
                }
                wg_commit();
                if ((u & 3) == 0 || u == 3) wg_wait<1>();
                if (u == 0) {
                    reg_fence<64>(aC);
                    if (lane == 0) mbar_arrive(bar + (B_GE + 3) * 8);
                    PROF(14);
                }
                if (u == 3 && lane == 0) mbar_arrive(bar + B_DE * 8);
                if ((u & 3) == 0) {
                    if (bt < 4) {
#pragma unroll
                        for (int i = 0; i < 8; i++) ldbox(G[(bt + 1) & 1][i], KSRC(bt * 8 + 8 + i));
                    } else {
#pragma unroll
                        for (int i = 1; i < 4; i++) ldgroup(CBUF(i), CSRC(i));
                    }
                }
                if (u < 8) GLU(aC, 32, u, offC, 10, C0[u >> 1]);
            }
        }
        PROF(15);
        {
            PHASE;
            const uint64_t dW = P.dB128[1];
#pragma unroll
            for (int i = 0; i < 4; i++) {
                mbar_wait(bar + (B_DF + 8 + i) * 8, 0);
                if (i > 0) chkgroup(CBUF(i), CSRC(i), tag);
                wg_fence();
#pragma unroll
                for (int k = 0; k < 4; k++) wgmma_rs_n64<true>(aS, CBUF(i)[k], dW + dsend(8 + i) * 64 + k * 128);
                wg_commit();
            }
            wg_fence();
#pragma unroll
            for (int k = 0; k < 4; k++) wgmma_rs_n64<true>(aK, C0[k], dW + dkeep(8) * 64 + k * 128);
            wg_commit();
            wg_wait<1>();
            reg_fence<32>(aS);
            PROF(16);
            pack_frag(own, aS);
            stgroup(g_part + (cta ^ 1) * 1024 + boxoff, own, tag);
            wg_fence();
#pragma unroll
            for (int i = 1; i < 4; i++)
#pragma unroll
                for (int k = 0; k < 4; k++) wgmma_rs_n64<true>(aK, CBUF(i)[k], dW + dkeep(8 + i) * 64 + k * 128);
            wg_commit();
#pragma unroll
            for (int k = 0; k < 4; k++) ldsm4(res[k], FRAG(0, k));
            pollgroup(own, g_part + cta * 1024 + boxoff, tag);
            PROF(17);
#pragma unroll
            for (int k = 0; k < 4; k++) set_frag(aS + 8 * k, res[k]);
            add_frag(aS, own);
            wg_wait<0>();
            reg_fence<32>(aK);
            PROF(18);
#pragma unroll
            for (int i = 0; i < 32; i++) aS[i] += aK[i];
            pack_frag(own, aS);
            __syncwarp();
#pragma unroll
            for (int k = 0; k < 4; k++) stsm4(FRAG(0, k), own[k]);
            __syncwarp();
#pragma unroll
            for (int i = 0; i < 4; i++) {
                const int row = i * 4 + (lane >> 3);
                uint32_t v[4];
                lds128(v, SB + SM_ACT + p * 8192 + (w * 16 + row) * 128 + (((lane & 7) ^ (row & 7)) << 4));
                *reinterpret_cast<uint4*>(P.out + (size_t)(g * 128 + 2 * (w * 16 + row) + p) * 512 + j * 64 + (lane & 7) * 8) = make_uint4(v[0], v[1], v[2], v[3]);
            }
            if (tid == 0) *(volatile unsigned*)&g_epoch[cta] = ep;
            PROF(19); PROFT(95); PROF_END;
        }
    }
}

typedef CUresult (*EncodeFn)(CUtensorMap*, CUtensorMapDataType, cuuint32_t, void*, const cuuint64_t*, const cuuint64_t*, const cuuint32_t*,
                             const cuuint32_t*, CUtensorMapInterleave, CUtensorMapSwizzle, CUtensorMapL2promotion, CUtensorMapFloatOOBfill);

void make_map(EncodeFn enc, CUtensorMap* m, const void* ptr, uint64_t cols, uint64_t rows, uint32_t bc, uint32_t br, CUtensorMapSwizzle sw,
              CUtensorMapL2promotion promo = CU_TENSOR_MAP_L2_PROMOTION_L2_128B) {
    cuuint64_t dims[2] = {cols, rows}, strides[1] = {cols * 2};
    cuuint32_t box[2] = {bc, br}, es[2] = {1, 1};
    enc(m, CU_TENSOR_MAP_DATA_TYPE_BFLOAT16, 2, const_cast<void*>(ptr), dims, strides, box, es, CU_TENSOR_MAP_INTERLEAVE_NONE, sw,
        promo, CU_TENSOR_MAP_FLOAT_OOB_FILL_NONE);
}

void make_map3(EncodeFn enc, CUtensorMap* m, const void* ptr, uint64_t rows, uint64_t parts) {
    cuuint64_t dims[3] = {512, rows, parts}, strides[2] = {parts * 1024, 1024};
    cuuint32_t box[3] = {64, 64, (cuuint32_t)parts}, es[3] = {1, 1, 1};
    CUresult r = enc(m, CU_TENSOR_MAP_DATA_TYPE_BFLOAT16, 3, const_cast<void*>(ptr), dims, strides, box, es, CU_TENSOR_MAP_INTERLEAVE_NONE,
        CU_TENSOR_MAP_SWIZZLE_128B, CU_TENSOR_MAP_L2_PROMOTION_L2_128B, CU_TENSOR_MAP_FLOAT_OOB_FILL_NONE);
    (void)r;
}

}

extern "C" void kernel_launch(void* const* d_in, const int* in_sizes, int n_in, void* d_out, int out_size) {
    static EncodeFn enc = nullptr;
    static int n_sm = 0;
    if (!enc) {
        int dev = 0;
        cudaGetDevice(&dev);
        cudaDeviceGetAttribute(&n_sm, cudaDevAttrMultiProcessorCount, dev);
        void* fn = nullptr;
        cudaDriverEntryPointQueryResult qr;
        cudaGetDriverEntryPoint("cuTensorMapEncodeTiled", &fn, cudaEnableDefault, &qr);
        enc = (EncodeFn)fn;
        cudaFuncSetAttribute(fused_block_kernel, cudaFuncAttributeMaxDynamicSharedMemorySize, SMEM_BYTES);
    }
    Params P;
    P.x = (const __nv_bfloat16*)d_in[0];
    P.wqkv = (const __nv_bfloat16*)d_in[1]; P.wo = (const __nv_bfloat16*)d_in[2];
    P.w1 = (const __nv_bfloat16*)d_in[4]; P.w3 = (const __nv_bfloat16*)d_in[5]; P.w2 = (const __nv_bfloat16*)d_in[6];
    P.out = (__nv_bfloat16*)d_out;
    make_map3(enc, &P.tmX, P.x, 1024, 2);
    make_map3(enc, &P.tmQKV, P.wqkv, 512, 3);
    make_map(enc, &P.tmWO, P.wo, 512, 512, 64, 256, CU_TENSOR_MAP_SWIZZLE_128B);
    make_map(enc, &P.tmW1, P.w1, 1792, 512, 64, 64, CU_TENSOR_MAP_SWIZZLE_128B);
    make_map(enc, &P.tmW3, P.w3, 1792, 512, 64, 64, CU_TENSOR_MAP_SWIZZLE_128B);
    make_map(enc, &P.tmW1h, P.w1, 1792, 512, 32, 64, CU_TENSOR_MAP_SWIZZLE_64B);
    make_map(enc, &P.tmW3h, P.w3, 1792, 512, 32, 64, CU_TENSOR_MAP_SWIZZLE_64B);
    make_map(enc, &P.tmW2, P.w2, 512, 1792, 64, 64, CU_TENSOR_MAP_SWIZZLE_128B);
    make_map(enc, &P.tmW2a, P.w2, 512, 1792, 64, 96, CU_TENSOR_MAP_SWIZZLE_128B);
    auto desc = [](uint64_t lbo, uint64_t sbo, uint64_t mode) { return (uint64_t)(SB >> 4) | (lbo >> 4) << 16 | (sbo >> 4) << 32 | mode << 62; };
    for (int i = 0; i < 4; i++) P.dB128[i] = desc(8192, 1024, 1);
    P.dB64 = desc(4096, 512, 2);
    P.dA[0] = P.dA[1] = desc(16, 1024, 1);
    P.by_smid = n_sm == 132;
    fused_block_kernel<<<P.by_smid ? 132 : 128, 384, SMEM_BYTES>>>(P);
}
```

```cpp
#include <cuda_runtime.h>
#include <cuda_bf16.h>
#include <cuda.h>
#include <stdint.h>

namespace {

constexpr uint32_t SM_ACT = 0, SM_RING = 131072, SM_CSQ = 229376, SM_WB = SM_CSQ + 768, SM_ST = SM_CSQ + 1024, SM_BAR = SM_CSQ + 2048;
constexpr uint32_t SMEM_BYTES = 232448;
constexpr uint32_t SB = 1024;
enum { B_XF = 0, B_WF = 8, B_WE = 12, B_OF = 16, B_GF = 17, B_GE = 23, B_DF = 29, B_DE = 37, B_CS1 = 38, B_WD = 39, B_OR = 40, B_PM = 41, B_L2 = 42, B_WB = 43, B_N = 44, B_EP = 44   };
constexpr uint32_t TAGM = 0x00010001u;
constexpr int LOOKAHEAD = 3, XAHEAD = 4;
constexpr int SPIN_LIMIT = 1 << 16;

constexpr int S_O = 0, S_H = 8192, S_HALO = 16384, S_ROWS = 18432  , S_STAT = 19456, S_EP = 19584, S_P = 19712,
              S_PART = S_P + 28672, GRP = S_PART + 24576;
__device__ uint4 g_scr[16 * GRP];
__device__ uint4 g_csq[128 * 48];
__device__ uint4 g_wb[256];
__device__ unsigned g_epoch[4];
#define PROF(slot)
#define PROFD(slot)
#define PROFE(slot)
#define PROFS(slot)
#define PROFT(slot)
#define PROF_ROLE(t)
#define PROF_START
#define PROF_END

struct Params {
    CUtensorMap tmX, tmQKV, tmWO, tmW1, tmW3, tmW1h, tmW3h, tmW2;
    const __nv_bfloat16 *x, *wqkv, *wo, *w1, *w3, *w2;
    __nv_bfloat16* out;
    uint64_t dB128[4], dB64, dA[2];
};

__device__ __forceinline__ void mbar_init(uint32_t bar, uint32_t cnt) { asm volatile("mbarrier.init.shared::cta.b64 [%0], %1;" ::"r"(bar), "r"(cnt) : "memory"); }
__device__ __forceinline__ void mbar_arrive(uint32_t bar) { asm volatile("mbarrier.arrive.shared::cta.b64 _, [%0];" ::"r"(bar) : "memory"); }
__device__ __forceinline__ void mbar_arrive_dep(uint32_t bar, uint32_t dep) {
    asm volatile("{\n.reg .b32 t;\nor.b32 t, %1, 1;\nmin.u32 t, t, 1;\nmbarrier.arrive.shared::cta.b64 _, [%0], t;\n}" ::"r"(bar), "r"(dep) : "memory");
}
__device__ __forceinline__ void mbar_wait(uint32_t bar, uint32_t parity) {
    asm volatile("{\n.reg .pred p;\n.reg .u32 n;\nmov.u32 n, 0;\n"
                 "LW:\nmbarrier.try_wait.parity.shared::cta.b64 p, [%0], %1;\n@p bra LD;\n"
                 "add.u32 n, n, 1;\nsetp.lt.u32 p, n, 262144;\n@p bra LW;\nLD:\n}" ::"r"(bar), "r"(parity) : "memory");
}
__device__ __forceinline__ void tma2d_e(uint32_t dst, const CUtensorMap* tm, int c0, int c1, uint32_t bar) {
    asm volatile("{\n.reg .pred p;\nelect.sync _|p, 0xffffffff;\n"
                 "@p cp.async.bulk.tensor.2d.shared::cluster.global.mbarrier::complete_tx::bytes [%0], [%1, {%3, %4}], [%2];\n}"
                 ::"r"(dst), "l"(tm), "r"(bar), "r"(c0), "r"(c1) : "memory");
}
__device__ __forceinline__ void tma3d_e(uint32_t dst, const CUtensorMap* tm, int c0, int c1, uint32_t bar) {
    asm volatile("{\n.reg .pred p;\nelect.sync _|p, 0xffffffff;\n"
                 "@p cp.async.bulk.tensor.3d.shared::cluster.global.mbarrier::complete_tx::bytes [%0], [%1, {%3, %4, 0}], [%2];\n}"
                 ::"r"(dst), "l"(tm), "r"(bar), "r"(c0), "r"(c1) : "memory");
}
__device__ __forceinline__ void mbar_expect_e(uint32_t bar, uint32_t bytes) {
    asm volatile("{\n.reg .pred p;\nelect.sync _|p, 0xffffffff;\n@p mbarrier.arrive.expect_tx.shared::cta.b64 _, [%0], %1;\n}" ::"r"(bar), "r"(bytes) : "memory");
}
__device__ __forceinline__ void wg_fence() { asm volatile("wgmma.fence.sync.aligned;" ::: "memory"); }
__device__ __forceinline__ void wg_commit() { asm volatile("wgmma.commit_group.sync.aligned;" ::: "memory"); }
template <int N> __device__ __forceinline__ void wg_wait() { asm volatile("wgmma.wait_group.sync.aligned %0;" ::"n"(N) : "memory"); }
template <int N> __device__ __forceinline__ void reg_fence(float* d) {
#pragma unroll
    for (int i = 0; i < N; i++) asm volatile("" : "+f"(d[i])::"memory");
}
__device__ __forceinline__ void ldsm4(uint32_t (&r)[4], uint32_t addr) {
    asm volatile("ldmatrix.sync.aligned.m8n8.x4.shared.b16 {%0,%1,%2,%3}, [%4];" : "=r"(r[0]), "=r"(r[1]), "=r"(r[2]), "=r"(r[3]) : "r"(addr) : "memory");
}
__device__ __forceinline__ void stsm4(uint32_t addr, const uint32_t (&r)[4]) {
    asm volatile("stmatrix.sync.aligned.m8n8.x4.shared.b16 [%0], {%1,%2,%3,%4};" ::"r"(addr), "r"(r[0]), "r"(r[1]), "r"(r[2]), "r"(r[3]) : "memory");
}
__device__ __forceinline__ uint32_t movm(uint32_t a) { uint32_t d; asm volatile("movmatrix.sync.aligned.m8n8.trans.b16 %0, %1;" : "=r"(d) : "r"(a)); return d; }
__device__ __forceinline__ void mma16(float (&d)[4], uint32_t a0, uint32_t a1, uint32_t a2, uint32_t a3, uint32_t b0, uint32_t b1, float c0 = 0.f) {
    asm volatile("mma.sync.aligned.m16n8k16.row.col.f32.bf16.bf16.f32 {%0,%1,%2,%3}, {%4,%5,%6,%7}, {%8,%9}, {%10,%10,%11,%11};"
                 : "=f"(d[0]), "=f"(d[1]), "=f"(d[2]), "=f"(d[3]) : "r"(a0), "r"(a1), "r"(a2), "r"(a3), "r"(b0), "r"(b1), "f"(c0), "f"(0.f));
}
__device__ __forceinline__ void mma8(float (&c)[4], uint32_t a0, uint32_t a1, uint32_t b0) {
    asm volatile("mma.sync.aligned.m16n8k8.row.col.f32.bf16.bf16.f32 {%0,%1,%2,%3}, {%4,%5}, {%6}, {%0,%1,%2,%3};"
                 : "+f"(c[0]), "+f"(c[1]), "+f"(c[2]), "+f"(c[3]) : "r"(a0), "r"(a1), "r"(b0));
}
__device__ __forceinline__ uint32_t pack2(float lo, float hi) { uint32_t r; asm("cvt.rn.bf16x2.f32 %0, %1, %2;" : "=r"(r) : "f"(hi), "f"(lo)); return r; }
__device__ __forceinline__ uint32_t badd2(uint32_t a, uint32_t b) { uint32_t r; asm("add.rn.bf16x2 %0, %1, %2;" : "=r"(r) : "r"(a), "r"(b)); return r; }
__device__ __forceinline__ float blo(uint32_t v) { return __uint_as_float(v << 16); }
__device__ __forceinline__ float bhi(uint32_t v) { return __uint_as_float(v & 0xffff0000u); }
__device__ __forceinline__ float ex2(float x) { float r; asm("ex2.approx.ftz.f32 %0, %1;" : "=f"(r) : "f"(x)); return r; }
__device__ __forceinline__ float rcp(float x) { float r; asm("rcp.approx.ftz.f32 %0, %1;" : "=f"(r) : "f"(x)); return r; }
__device__ __forceinline__ float rsq(float x) { float r; asm("rsqrt.approx.ftz.f32 %0, %1;" : "=f"(r) : "f"(x)); return r; }
__device__ __forceinline__ float2 lds64(uint32_t a) { float2 v; asm volatile("ld.shared.v2.f32 {%0,%1}, [%2];" : "=f"(v.x), "=f"(v.y) : "r"(a)); return v; }
__device__ __forceinline__ void lds128(uint32_t (&v)[4], uint32_t a) {
    asm volatile("ld.shared.v4.u32 {%0,%1,%2,%3}, [%4];" : "=r"(v[0]), "=r"(v[1]), "=r"(v[2]), "=r"(v[3]) : "r"(a) : "memory");
}
__device__ __forceinline__ void ldbox(uint32_t (&r)[4], const uint4* p) {
    asm volatile("{\n.reg .b128 t;\nld.relaxed.gpu.global.b128 t, [%4];\nmov.b128 {%0,%1,%2,%3}, t;\n}"
                 : "=r"(r[0]), "=r"(r[1]), "=r"(r[2]), "=r"(r[3]) : "l"(p) : "memory");
}
__device__ __forceinline__ void stbox(uint4* p, uint32_t a, uint32_t b, uint32_t c, uint32_t d) {
    asm volatile("{\n.reg .b128 t;\nmov.b128 t, {%1,%2,%3,%4};\nst.relaxed.gpu.global.b128 [%0], t;\n}" ::"l"(p), "r"(a), "r"(b), "r"(c), "r"(d) : "memory");
}
__device__ __forceinline__ void clrbox(uint4* p) { stbox(p, 0, 0, 0, 0); }
__device__ __forceinline__ void ldgroup(uint32_t (&v)[4][4], const uint4* p) {
#pragma unroll
    for (int i = 0; i < 4; i++) ldbox(v[i], p + i * 32);
}
__device__ __forceinline__ void stgroup(uint4* p, uint32_t (&v)[4][4], uint32_t tag) {
#pragma unroll
    for (int i = 0; i < 4; i++) {
        v[i][0] = (v[i][0] & ~TAGM) | tag;
        stbox(p + i * 32, v[i][0], v[i][1], v[i][2], v[i][3]);
    }
}
__device__ __forceinline__ bool badgroup(const uint32_t (&v)[4][4], uint32_t tag) {
    return __any_sync(0xffffffffu, (((v[0][0] ^ tag) | (v[1][0] ^ tag) | (v[2][0] ^ tag) | (v[3][0] ^ tag)) & TAGM) != 0);
}
__device__ __forceinline__ void chkgroup(uint32_t (&v)[4][4], const uint4* p, uint32_t tag) {
    if (__builtin_expect(badgroup(v, tag), 0)) {
        int n = 0;
        do ldgroup(v, p); while (badgroup(v, tag) && ++n < SPIN_LIMIT);
    }
}
__device__ __forceinline__ void pollgroup(uint32_t (&v)[4][4], const uint4* p, uint32_t tag) {
    int n = 0;
    while (true) {
        ldgroup(v, p);
        uint32_t bad = ((v[0][0] ^ tag) | (v[1][0] ^ tag) | (v[2][0] ^ tag) | (v[3][0] ^ tag)) & TAGM;
        if (!__any_sync(0xffffffffu, bad != 0) || ++n > SPIN_LIMIT) break;
    }
}
__device__ __forceinline__ void wgmma_rs_n64_reuse(float* d, const uint32_t (&a)[4], uint64_t db) {
    asm volatile("wgmma.mma_async.sync.aligned.m64n64k16.f32.bf16.bf16 "
            "{%0, %1, %2, %3, %4, %5, %6, %7, %8, %9, %10, %11, %12, %13, %14, %15, %16, %17, %18, %19, %20, %21, %22, %23, %24, %25, %26, %27, %28, %29, %30, %31}, "
            "{%32, %33, %34, %35}, %36, 0, 1, 1, 1;"
            : "+f"(d[0]), "+f"(d[1]), "+f"(d[2]), "+f"(d[3]), "+f"(d[4]), "+f"(d[5]), "+f"(d[6]), "+f"(d[7]),
              "+f"(d[8]), "+f"(d[9]), "+f"(d[10]), "+f"(d[11]), "+f"(d[12]), "+f"(d[13]), "+f"(d[14]), "+f"(d[15]),
              "+f"(d[16]), "+f"(d[17]), "+f"(d[18]), "+f"(d[19]), "+f"(d[20]), "+f"(d[21]), "+f"(d[22]), "+f"(d[23]),
              "+f"(d[24]), "+f"(d[25]), "+f"(d[26]), "+f"(d[27]), "+f"(d[28]), "+f"(d[29]), "+f"(d[30]), "+f"(d[31])
            : "r"(a[0]), "r"(a[1]), "r"(a[2]), "r"(a[3]), "l"(db));
}
template <bool ACC>
__device__ __forceinline__ void wgmma_rs_n64(float* d, const uint32_t (&a)[4], uint64_t db) {
    if constexpr (ACC) {
        asm volatile("wgmma.mma_async.sync.aligned.m64n64k16.f32.bf16.bf16 "
            "{%0, %1, %2, %3, %4, %5, %6, %7, %8, %9, %10, %11, %12, %13, %14, %15, %16, %17, %18, %19, %20, %21, %22, %23, %24, %25, %26, %27, %28, %29, %30, %31}, "
            "{%32, %33, %34, %35}, %36, 1, 1, 1, 1;"
            : "+f"(d[0]), "+f"(d[1]), "+f"(d[2]), "+f"(d[3]), "+f"(d[4]), "+f"(d[5]), "+f"(d[6]), "+f"(d[7]),
              "+f"(d[8]), "+f"(d[9]), "+f"(d[10]), "+f"(d[11]), "+f"(d[12]), "+f"(d[13]), "+f"(d[14]), "+f"(d[15]),
              "+f"(d[16]), "+f"(d[17]), "+f"(d[18]), "+f"(d[19]), "+f"(d[20]), "+f"(d[21]), "+f"(d[22]), "+f"(d[23]),
              "+f"(d[24]), "+f"(d[25]), "+f"(d[26]), "+f"(d[27]), "+f"(d[28]), "+f"(d[29]), "+f"(d[30]), "+f"(d[31])
            : "r"(a[0]), "r"(a[1]), "r"(a[2]), "r"(a[3]), "l"(db));
    } else {
        asm volatile("wgmma.mma_async.sync.aligned.m64n64k16.f32.bf16.bf16 "
            "{%0, %1, %2, %3, %4, %5, %6, %7, %8, %9, %10, %11, %12, %13, %14, %15, %16, %17, %18, %19, %20, %21, %22, %23, %24, %25, %26, %27, %28, %29, %30, %31}, "
            "{%32, %33, %34, %35}, %36, 0, 1, 1, 1;"
            : "=f"(d[0]), "=f"(d[1]), "=f"(d[2]), "=f"(d[3]), "=f"(d[4]), "=f"(d[5]), "=f"(d[6]), "=f"(d[7]),
              "=f"(d[8]), "=f"(d[9]), "=f"(d[10]), "=f"(d[11]), "=f"(d[12]), "=f"(d[13]), "=f"(d[14]), "=f"(d[15]),
              "=f"(d[16]), "=f"(d[17]), "=f"(d[18]), "=f"(d[19]), "=f"(d[20]), "=f"(d[21]), "=f"(d[22]), "=f"(d[23]),
              "=f"(d[24]), "=f"(d[25]), "=f"(d[26]), "=f"(d[27]), "=f"(d[28]), "=f"(d[29]), "=f"(d[30]), "=f"(d[31])
            : "r"(a[0]), "r"(a[1]), "r"(a[2]), "r"(a[3]), "l"(db));
    }
}
template <bool ACC>
__device__ __forceinline__ void wgmma_rs_n128(float* d, const uint32_t (&a)[4], uint64_t db) {
    if constexpr (ACC) {
        asm volatile("wgmma.mma_async.sync.aligned.m64n128k16.f32.bf16.bf16 "
            "{%0, %1, %2, %3, %4, %5, %6, %7, %8, %9, %10, %11, %12, %13, %14, %15, %16, %17, %18, %19, %20, %21, %22, %23, %24, %25, %26, %27, %28, %29, %30, %31, %32, %33, %34, %35, %36, %37, %38, %39, %40, %41, %42, %43, %44, %45, %46, %47, %48, %49, %50, %51, %52, %53, %54, %55, %56, %57, %58, %59, %60, %61, %62, %63}, "
            "{%64, %65, %66, %67}, %68, 1, 1, 1, 1;"
            : "+f"(d[0]), "+f"(d[1]), "+f"(d[2]), "+f"(d[3]), "+f"(d[4]), "+f"(d[5]), "+f"(d[6]), "+f"(d[7]),
              "+f"(d[8]), "+f"(d[9]), "+f"(d[10]), "+f"(d[11]), "+f"(d[12]), "+f"(d[13]), "+f"(d[14]), "+f"(d[15]),
              "+f"(d[16]), "+f"(d[17]), "+f"(d[18]), "+f"(d[19]), "+f"(d[20]), "+f"(d[21]), "+f"(d[22]), "+f"(d[23]),
              "+f"(d[24]), "+f"(d[25]), "+f"(d[26]), "+f"(d[27]), "+f"(d[28]), "+f"(d[29]), "+f"(d[30]), "+f"(d[31]),
              "+f"(d[32]), "+f"(d[33]), "+f"(d[34]), "+f"(d[35]), "+f"(d[36]), "+f"(d[37]), "+f"(d[38]), "+f"(d[39]),
              "+f"(d[40]), "+f"(d[41]), "+f"(d[42]), "+f"(d[43]), "+f"(d[44]), "+f"(d[45]), "+f"(d[46]), "+f"(d[47]),
              "+f"(d[48]), "+f"(d[49]), "+f"(d[50]), "+f"(d[51]), "+f"(d[52]), "+f"(d[53]), "+f"(d[54]), "+f"(d[55]),
              "+f"(d[56]), "+f"(d[57]), "+f"(d[58]), "+f"(d[59]), "+f"(d[60]), "+f"(d[61]), "+f"(d[62]), "+f"(d[63])
            : "r"(a[0]), "r"(a[1]), "r"(a[2]), "r"(a[3]), "l"(db));
    } else {
        asm volatile("wgmma.mma_async.sync.aligned.m64n128k16.f32.bf16.bf16 "
            "{%0, %1, %2, %3, %4, %5, %6, %7, %8, %9, %10, %11, %12, %13, %14, %15, %16, %17, %18, %19, %20, %21, %22, %23, %24, %25, %26, %27, %28, %29, %30, %31, %32, %33, %34, %35, %36, %37, %38, %39, %40, %41, %42, %43, %44, %45, %46, %47, %48, %49, %50, %51, %52, %53, %54, %55, %56, %57, %58, %59, %60, %61, %62, %63}, "
            "{%64, %65, %66, %67}, %68, 0, 1, 1, 1;"
            : "=f"(d[0]), "=f"(d[1]), "=f"(d[2]), "=f"(d[3]), "=f"(d[4]), "=f"(d[5]), "=f"(d[6]), "=f"(d[7]),
              "=f"(d[8]), "=f"(d[9]), "=f"(d[10]), "=f"(d[11]), "=f"(d[12]), "=f"(d[13]), "=f"(d[14]), "=f"(d[15]),
              "=f"(d[16]), "=f"(d[17]), "=f"(d[18]), "=f"(d[19]), "=f"(d[20]), "=f"(d[21]), "=f"(d[22]), "=f"(d[23]),
              "=f"(d[24]), "=f"(d[25]), "=f"(d[26]), "=f"(d[27]), "=f"(d[28]), "=f"(d[29]), "=f"(d[30]), "=f"(d[31]),
              "=f"(d[32]), "=f"(d[33]), "=f"(d[34]), "=f"(d[35]), "=f"(d[36]), "=f"(d[37]), "=f"(d[38]), "=f"(d[39]),
              "=f"(d[40]), "=f"(d[41]), "=f"(d[42]), "=f"(d[43]), "=f"(d[44]), "=f"(d[45]), "=f"(d[46]), "=f"(d[47]),
              "=f"(d[48]), "=f"(d[49]), "=f"(d[50]), "=f"(d[51]), "=f"(d[52]), "=f"(d[53]), "=f"(d[54]), "=f"(d[55]),
              "=f"(d[56]), "=f"(d[57]), "=f"(d[58]), "=f"(d[59]), "=f"(d[60]), "=f"(d[61]), "=f"(d[62]), "=f"(d[63])
            : "r"(a[0]), "r"(a[1]), "r"(a[2]), "r"(a[3]), "l"(db));
    }
}
template <bool ACC>
__device__ __forceinline__ void wgmma_ss_n64(float* d, uint64_t da, uint64_t db) {
    if constexpr (ACC) {
        asm volatile("wgmma.mma_async.sync.aligned.m64n64k16.f32.bf16.bf16 "
            "{%0, %1, %2, %3, %4, %5, %6, %7, %8, %9, %10, %11, %12, %13, %14, %15, %16, %17, %18, %19, %20, %21, %22, %23, %24, %25, %26, %27, %28, %29, %30, %31}, "
            "%32, %33, 1, 1, 1, 0, 1;"
            : "+f"(d[0]), "+f"(d[1]), "+f"(d[2]), "+f"(d[3]), "+f"(d[4]), "+f"(d[5]), "+f"(d[6]), "+f"(d[7]),
              "+f"(d[8]), "+f"(d[9]), "+f"(d[10]), "+f"(d[11]), "+f"(d[12]), "+f"(d[13]), "+f"(d[14]), "+f"(d[15]),
              "+f"(d[16]), "+f"(d[17]), "+f"(d[18]), "+f"(d[19]), "+f"(d[20]), "+f"(d[21]), "+f"(d[22]), "+f"(d[23]),
              "+f"(d[24]), "+f"(d[25]), "+f"(d[26]), "+f"(d[27]), "+f"(d[28]), "+f"(d[29]), "+f"(d[30]), "+f"(d[31])
            : "l"(da), "l"(db));
    } else {
        asm volatile("wgmma.mma_async.sync.aligned.m64n64k16.f32.bf16.bf16 "
            "{%0, %1, %2, %3, %4, %5, %6, %7, %8, %9, %10, %11, %12, %13, %14, %15, %16, %17, %18, %19, %20, %21, %22, %23, %24, %25, %26, %27, %28, %29, %30, %31}, "
            "%32, %33, 0, 1, 1, 0, 1;"
            : "=f"(d[0]), "=f"(d[1]), "=f"(d[2]), "=f"(d[3]), "=f"(d[4]), "=f"(d[5]), "=f"(d[6]), "=f"(d[7]),
              "=f"(d[8]), "=f"(d[9]), "=f"(d[10]), "=f"(d[11]), "=f"(d[12]), "=f"(d[13]), "=f"(d[14]), "=f"(d[15]),
              "=f"(d[16]), "=f"(d[17]), "=f"(d[18]), "=f"(d[19]), "=f"(d[20]), "=f"(d[21]), "=f"(d[22]), "=f"(d[23]),
              "=f"(d[24]), "=f"(d[25]), "=f"(d[26]), "=f"(d[27]), "=f"(d[28]), "=f"(d[29]), "=f"(d[30]), "=f"(d[31])
            : "l"(da), "l"(db));
    }
}
template <bool ACC>
__device__ __forceinline__ void wgmma_ss_n128(float* d, uint64_t da, uint64_t db) {
    if constexpr (ACC) {
        asm volatile("wgmma.mma_async.sync.aligned.m64n128k16.f32.bf16.bf16 "
            "{%0, %1, %2, %3, %4, %5, %6, %7, %8, %9, %10, %11, %12, %13, %14, %15, %16, %17, %18, %19, %20, %21, %22, %23, %24, %25, %26, %27, %28, %29, %30, %31, %32, %33, %34, %35, %36, %37, %38, %39, %40, %41, %42, %43, %44, %45, %46, %47, %48, %49, %50, %51, %52, %53, %54, %55, %56, %57, %58, %59, %60, %61, %62, %63}, "
            "%64, %65, 1, 1, 1, 0, 1;"
            : "+f"(d[0]), "+f"(d[1]), "+f"(d[2]), "+f"(d[3]), "+f"(d[4]), "+f"(d[5]), "+f"(d[6]), "+f"(d[7]),
              "+f"(d[8]), "+f"(d[9]), "+f"(d[10]), "+f"(d[11]), "+f"(d[12]), "+f"(d[13]), "+f"(d[14]), "+f"(d[15]),
              "+f"(d[16]), "+f"(d[17]), "+f"(d[18]), "+f"(d[19]), "+f"(d[20]), "+f"(d[21]), "+f"(d[22]), "+f"(d[23]),
              "+f"(d[24]), "+f"(d[25]), "+f"(d[26]), "+f"(d[27]), "+f"(d[28]), "+f"(d[29]), "+f"(d[30]), "+f"(d[31]),
              "+f"(d[32]), "+f"(d[33]), "+f"(d[34]), "+f"(d[35]), "+f"(d[36]), "+f"(d[37]), "+f"(d[38]), "+f"(d[39]),
              "+f"(d[40]), "+f"(d[41]), "+f"(d[42]), "+f"(d[43]), "+f"(d[44]), "+f"(d[45]), "+f"(d[46]), "+f"(d[47]),
              "+f"(d[48]), "+f"(d[49]), "+f"(d[50]), "+f"(d[51]), "+f"(d[52]), "+f"(d[53]), "+f"(d[54]), "+f"(d[55]),
              "+f"(d[56]), "+f"(d[57]), "+f"(d[58]), "+f"(d[59]), "+f"(d[60]), "+f"(d[61]), "+f"(d[62]), "+f"(d[63])
            : "l"(da), "l"(db));
    } else {
        asm volatile("wgmma.mma_async.sync.aligned.m64n128k16.f32.bf16.bf16 "
            "{%0, %1, %2, %3, %4, %5, %6, %7, %8, %9, %10, %11, %12, %13, %14, %15, %16, %17, %18, %19, %20, %21, %22, %23, %24, %25, %26, %27, %28, %29, %30, %31, %32, %33, %34, %35, %36, %37, %38, %39, %40, %41, %42, %43, %44, %45, %46, %47, %48, %49, %50, %51, %52, %53, %54, %55, %56, %57, %58, %59, %60, %61, %62, %63}, "
            "%64, %65, 0, 1, 1, 0, 1;"
            : "=f"(d[0]), "=f"(d[1]), "=f"(d[2]), "=f"(d[3]), "=f"(d[4]), "=f"(d[5]), "=f"(d[6]), "=f"(d[7]),
              "=f"(d[8]), "=f"(d[9]), "=f"(d[10]), "=f"(d[11]), "=f"(d[12]), "=f"(d[13]), "=f"(d[14]), "=f"(d[15]),
              "=f"(d[16]), "=f"(d[17]), "=f"(d[18]), "=f"(d[19]), "=f"(d[20]), "=f"(d[21]), "=f"(d[22]), "=f"(d[23]),
              "=f"(d[24]), "=f"(d[25]), "=f"(d[26]), "=f"(d[27]), "=f"(d[28]), "=f"(d[29]), "=f"(d[30]), "=f"(d[31]),
              "=f"(d[32]), "=f"(d[33]), "=f"(d[34]), "=f"(d[35]), "=f"(d[36]), "=f"(d[37]), "=f"(d[38]), "=f"(d[39]),
              "=f"(d[40]), "=f"(d[41]), "=f"(d[42]), "=f"(d[43]), "=f"(d[44]), "=f"(d[45]), "=f"(d[46]), "=f"(d[47]),
              "=f"(d[48]), "=f"(d[49]), "=f"(d[50]), "=f"(d[51]), "=f"(d[52]), "=f"(d[53]), "=f"(d[54]), "=f"(d[55]),
              "=f"(d[56]), "=f"(d[57]), "=f"(d[58]), "=f"(d[59]), "=f"(d[60]), "=f"(d[61]), "=f"(d[62]), "=f"(d[63])
            : "l"(da), "l"(db));
    }
}

__device__ __forceinline__ float silu_mul(float g, float u, float k, float v) { return g * u * rcp(fmaf(ex2(g * k), v, v)); }
__device__ __forceinline__ void glu_tile(const float* g, const float* u, float k0, float k1, float v0, float v1, uint32_t& o0, uint32_t& o1) {
    o0 = pack2(silu_mul(g[0], u[0], k0, v0), silu_mul(g[1], u[1], k0, v0));
    o1 = pack2(silu_mul(g[2], u[2], k1, v1), silu_mul(g[3], u[3], k1, v1));
}

__device__ __forceinline__ float quad_sum(float v) {
    v += __shfl_xor_sync(0xffffffffu, v, 1);
    return v + __shfl_xor_sync(0xffffffffu, v, 2);
}

__device__ __forceinline__ void put_rows(uint4* box, int c, float a0, float a1, unsigned ep) {
    a0 = quad_sum(a0); a1 = quad_sum(a1);
    if (c == 0) stbox(box, __float_as_uint(a0), ep, __float_as_uint(a1), ep);
}
__device__ __forceinline__ float2 sum_rows(const uint4* sp, unsigned ep) {
    uint32_t v[8][4], bad;
    int n = 0;
    do {
        bad = 0;
#pragma unroll
        for (int i = 0; i < 8; i++) ldbox(v[i], sp + i * 64);
#pragma unroll
        for (int i = 0; i < 8; i++) bad |= (v[i][1] ^ ep) | (v[i][3] ^ ep);
    } while (bad && ++n < SPIN_LIMIT);
    float2 t = make_float2(0.f, 0.f);
#pragma unroll
    for (int i = 0; i < 8; i++) { t.x += __uint_as_float(v[i][0]); t.y += __uint_as_float(v[i][2]); }
    return t;
}

template <int STRIDE>
__device__ __forceinline__ void colsum8(float (&s)[8], const uint4* q) {
    uint4 v[8];
#pragma unroll
    for (int i = 0; i < 8; i++)
        asm volatile("ld.global.nc.v4.u32 {%0,%1,%2,%3}, [%4];" : "=r"(v[i].x), "=r"(v[i].y), "=r"(v[i].z), "=r"(v[i].w) : "l"(q + i * STRIDE) : "memory");
#pragma unroll
    for (int i = 0; i < 8; i++) {
        if (i == 0) {
            s[0] = blo(v[i].x); s[1] = bhi(v[i].x); s[2] = blo(v[i].y); s[3] = bhi(v[i].y);
            s[4] = blo(v[i].z); s[5] = bhi(v[i].z); s[6] = blo(v[i].w); s[7] = bhi(v[i].w);
        } else {
            s[0] += blo(v[i].x); s[1] += bhi(v[i].x); s[2] += blo(v[i].y); s[3] += bhi(v[i].y);
            s[4] += blo(v[i].z); s[5] += bhi(v[i].z); s[6] += blo(v[i].w); s[7] += bhi(v[i].w);
        }
    }
}
template <int STRIDE>
__device__ __forceinline__ void gather8(float (&t)[4], const uint4* q, uint32_t tag) {
    uint32_t v[8][4];
    int n = 0;
    uint32_t bad;
    do {
        bad = 0;
#pragma unroll
        for (int i = 0; i < 8; i++) ldbox(v[i], q + i * STRIDE);
#pragma unroll
        for (int i = 0; i < 8; i++) bad |= v[i][0] ^ tag;
    } while ((bad & 3u) && ++n < SPIN_LIMIT);
#pragma unroll
    for (int i = 0; i < 8; i++)
#pragma unroll
        for (int k = 0; k < 4; k++) t[k] += __uint_as_float(v[i][k]);
}
__device__ __forceinline__ int kc_at(int j, int d) { return d == 0 ? j : d - 1 + (d - 1 >= j); }
__device__ __forceinline__ void add_frag(float (&a)[32], const uint32_t (&in)[4][4]) {
#pragma unroll
    for (int i = 0; i < 16; i++) { a[2 * i] += blo(in[i >> 2][i & 3]); a[2 * i + 1] += bhi(in[i >> 2][i & 3]); }
}
__device__ __forceinline__ void pack_frag(uint32_t (&o)[4][4], const float (&a)[32]) {
#pragma unroll
    for (int i = 0; i < 8; i++) { o[i >> 1][(i & 1) * 2] = pack2(a[4 * i], a[4 * i + 1]); o[i >> 1][(i & 1) * 2 + 1] = pack2(a[4 * i + 2], a[4 * i + 3]); }
}
__host__ __device__ constexpr uint32_t oland(int d) { return (d == 2 ? 0 : d + 2) * 16384; }
__host__ __device__ constexpr uint32_t dtile(int i) { return i == 0 || i == 7 ? 192 : i == 1 ? 128 : i == 2 ? 160 : 16 + (i - 3) * 28; }

template <bool BY_SMID>
__global__ void __launch_bounds__(384, 1) fused_block_kernel(const __grid_constant__ Params P) {
    extern __shared__ __align__(1024) unsigned char smem_raw[];
    if ((uint32_t)__cvta_generic_to_shared(smem_raw) != SB) return;
    constexpr uint32_t bar = SB + SM_BAR;
    const int tid = threadIdx.x, lane = tid & 31;
    int cta = blockIdx.x;
    if (BY_SMID) {
        unsigned sm, nsm;
        asm("mov.u32 %0, %%smid;" : "=r"(sm));
        asm("mov.u32 %0, %%nsmid;" : "=r"(nsm));
        if (nsm != 132) sm = blockIdx.x;
        if (sm - 120u < 4u) {
            const unsigned ep = *(volatile unsigned*)&g_epoch[sm - 120] + 1;
            if (tid < 128) {
                uint32_t v[4];
                int n = 0;
                do ldbox(v, g_csq + tid * 48); while (((v[0] ^ ((ep & 1) ? 1u : 2u)) & 3u) && ++n < SPIN_LIMIT);
            }
            __syncthreads();
            if (tid == 0) *(volatile unsigned*)&g_epoch[sm - 120] = ep;
            return;
        }
        const int q = sm < 64 ? (sm & 15) >> 1 : sm < 120 ? 1 + ((sm - 64) % 14 >> 1) : 0;
        const int rk = sm < 64 ? (sm >> 4) * 2 + (sm & 1) : sm < 120 ? 8 + (sm - 64) / 14 * 2 + (sm & 1) : sm - 116;
        cta = ((q >> 1) * 4 + (rk >> 2)) * 8 + (rk & 3) * 2 + (q & 1);
    }
    cta = __shfl_sync(0xffffffffu, cta, 0);
    const int g = cta >> 3, j = cta & 7;
    const int warp = __shfl_sync(0xffffffffu, tid >> 5, 0);
    const int qd = j & 1, offA64 = qd ? 32 : 128, offA32 = qd ? 0 : 192, offB = qd ? 96 : 64, offC = qd ? 160 : 0;
    PROF_START;
    if (tid < 48) asm volatile("prefetch.global.L2 [%0];" ::"l"(P.x + (cta * 16 + tid / 3) * 512 + tid % 3 * 64));

    auto load_x = [&](int d) {
        mbar_expect_e(bar + (B_XF + d) * 8, 16384);
        tma3d_e(SB + SM_ACT + d * 16384, &P.tmX, d * 64, g * 64, bar + (B_XF + d) * 8);
    };
    auto load_wqkv = [&](int d) {
        mbar_expect_e(bar + (B_WF + (d & 3)) * 8, 24576);
        tma3d_e(SB + SM_RING + (d & 3) * 24576, &P.tmQKV, j * 64, d * 64, bar + (B_WF + (d & 3)) * 8);
    };
    auto init_bars = [&](bool early) {
        if (lane == 0) {
#pragma unroll
            for (int i = 0; i < B_N; i++) {
                const bool e8 = (i >= B_WE && i < B_OF) || (i >= B_GE && i < B_DF) || i == B_DE || i == B_WD || i == B_OR;
                const bool first = (i >= B_XF && i < B_XF + LOOKAHEAD) || (i >= B_WF && i < B_WF + LOOKAHEAD);
                if (first == early) mbar_init(bar + i * 8, e8 ? 8 : i == B_CS1 ? 3 : i == B_PM || i == B_L2 ? 2 : 1);
            }
            asm volatile("fence.proxy.async.shared::cta;" ::: "memory");
        }
        __syncwarp();
    };
    if (warp >= 8) {
        asm volatile("setmaxnreg.dec.sync.aligned.u32 56;");
        if (warp == 8) {
            PROF_ROLE(256);
            init_bars(true);
            asm volatile("bar.arrive 0, 320;" ::: "memory");
            PROFS(21);
#pragma unroll
            for (int d = 0; d < LOOKAHEAD; d++) {
                load_x(d); load_wqkv(d);
                if (d == 0) asm volatile("bar.arrive 9, 128;" ::: "memory");
            }
            asm volatile("bar.sync 8, 64;" ::: "memory");
            const int f0 = j * 224;
#pragma unroll 1
            for (int d = LOOKAHEAD; d < 8; d++) {
                mbar_wait(bar + (B_WF + ((d - LOOKAHEAD) & 3)) * 8, (d - LOOKAHEAD) >> 2);
#pragma unroll 1
                for (int e = d == LOOKAHEAD ? d : d + XAHEAD; e <= d + XAHEAD && e < 8; e++) load_x(e);
                if (d >= 4) mbar_wait(bar + (B_WE + (d & 3)) * 8, 0);
                load_wqkv(d);
                PROFD(32 + d);
            }
            mbar_wait(bar + (B_WE + 3) * 8, 1);
            mbar_expect_e(bar + B_OF * 8, 65536);
            tma2d_e(SB + SM_ACT + 16384, &P.tmWO, j * 64, 0, bar + B_OF * 8);
            tma2d_e(SB + SM_ACT + 49152, &P.tmWO, j * 64, 256, bar + B_OF * 8);
            PROF(40);
#pragma unroll 1
            for (int d = 0; d < 8; d++) {
                const uint32_t dst = SB + SM_RING + (d & 3) * 24576, fb = bar + (B_WF + (d & 3)) * 8;
                const int row = kc_at(j, d) * 64;
                if (d >= 4) mbar_wait(bar + (B_WE + (d & 3)) * 8, 0);
                else mbar_wait(d == 0 ? bar + B_OF * 8 : fb - 8, 0);
                mbar_expect_e(fb, 24576);
                tma2d_e(dst, &P.tmW1, f0 + offA64, row, fb);
                tma2d_e(dst + 8192, &P.tmW3, f0 + offA64, row, fb);
                tma2d_e(dst + 16384, &P.tmW1h, f0 + offA32, row, fb);
                tma2d_e(dst + 20480, &P.tmW3h, f0 + offA32, row, fb);
            }
            auto load_w2 = [&](int i) {
                const uint32_t fb = bar + (B_DF + i) * 8;
                if (i < 3) mbar_wait(bar + (B_GE + ((0x315 >> (4 * i)) & 7)) * 8, i == 0);
                if (i == 7) mbar_wait(bar + B_DE * 8, 0);
                if (i >= 4) mbar_wait(fb - 16, 0);
                mbar_expect_e(fb, 28672);
                tma2d_e(SB + dtile(i) * 1024, &P.tmW2, ((j & 4) + ((j + 1 + (i >> 1)) & 3)) * 64, (j ^ (i & 1) * 4) * 224, fb);
            };
#pragma unroll 1
            for (int n = 0; n < 16; n++) {
                const int sl = n % 6;
                const uint32_t dst = SB + SM_RING + sl * 16384, fb = bar + (B_GF + sl) * 8;
                const int row = kc_at(j, n & 7) * 64, col = f0 + (n < 8 ? offB : offC);
                mbar_wait(bar + (n < 6 ? B_WE + ((0x332110 >> (4 * n)) & 3) : B_GE + sl) * 8, n < 6 || n >= 12);
                mbar_expect_e(fb, 16384);
                tma2d_e(dst, &P.tmW1, col, row, fb);
                tma2d_e(dst + 8192, &P.tmW3, col, row, fb);
            }
#pragma unroll 1
            for (int i = 0; i < 8; i++) load_w2(i);
            PROF_END;
        } else {
            PROF_ROLE(PHLP);
            const int hw = warp - 9;
            uint4* const gs = g_scr + g * GRP;
            if (hw == 0) {
                init_bars(false);
                asm volatile("bar.arrive 0, 320;\nbar.arrive 8, 64;" ::: "memory");
            }
            unsigned ep;
            asm volatile("ld.relaxed.gpu.global.u32 %0, [%1];" : "=r"(ep) : "l"(reinterpret_cast<unsigned*>(gs + S_EP) + j));
            if (hw == 1 && !(lane & 2)) clrbox(gs + S_STAT + j * 16 + (lane >> 2) + (lane & 1) * 8);
            if (hw == 2 && lane < 2) clrbox(g_wb + cta * 2 + lane);
            asm volatile("bar.sync 9, 128;" ::: "memory");
            uint32_t tag;
            {
                float s[8];
                const uint4* q = reinterpret_cast<const uint4*>(P.wqkv + (g * 32 + (lane >> 3)) * 1536 + hw * 512 + j * 64) + (lane & 7);
                colsum8<4 * 192>(s, q);
                ep += 1;
                tag = (ep & 1) ? 1u : 2u;
                const bool b4 = lane & 16;
                float t[4];
#pragma unroll
                for (int i = 0; i < 4; i++) {
                    t[i] = (b4 ? s[i + 4] : s[i]) + __shfl_xor_sync(0xffffffffu, b4 ? s[i] : s[i + 4], 16);
                    t[i] += __shfl_xor_sync(0xffffffffu, t[i], 8);
                }
                if (!(lane & 8))
                    stbox(g_csq + (cta * 3 + hw) * 16 + (lane & 7) * 2 + (lane >> 4), (__float_as_uint(t[0]) & ~3u) | tag, __float_as_uint(t[1]), __float_as_uint(t[2]), __float_as_uint(t[3]));
            }
            PROF(42);
            if (hw == 2) asm volatile("prefetch.global.L2 [%0];" ::"l"(P.wo + (j * 64 + g * 4) * 512 + lane * 64));
            {
                const uint32_t fr = SB + SM_ACT + j * 2048 + (lane & 15) * 128 + (((lane >> 4) ^ (lane & 7)) << 4);
                float s0 = 0.f, q0 = 0.f, s1 = 0.f, q1 = 0.f;
                uint32_t nx[4][4];
                mbar_wait(bar + (B_XF + hw) * 8, 0);
#pragma unroll
                for (int k = 0; k < 4; k++) ldsm4(nx[k], (fr ^ (k * 32)) + hw * 16384);
#pragma unroll 1
                for (int d = hw + 3; d < 11; d += 3) {
                    uint32_t a[4][4];
#pragma unroll
                    for (int k = 0; k < 4; k++)
#pragma unroll
                        for (int i = 0; i < 4; i++) asm volatile("mov.b32 %0, %1;" : "=r"(a[k][i]) : "r"(nx[k][i]));
                    if (d < 8) {
                        mbar_wait(bar + (B_XF + d) * 8, 0);
#pragma unroll
                        for (int k = 0; k < 4; k++) ldsm4(nx[k], (fr ^ (k * 32)) + d * 16384);
                    }
#pragma unroll
                    for (int k = 0; k < 4; k++)
#pragma unroll
                        for (int h = 0; h < 2; h++) {
                            const float x0 = blo(a[k][2 * h]), x1 = bhi(a[k][2 * h]), y0 = blo(a[k][2 * h + 1]), y1 = bhi(a[k][2 * h + 1]);
                            s0 += x0 + x1; q0 = fmaf(x0, x0, q0); q0 = fmaf(x1, x1, q0);
                            s1 += y0 + y1; q1 = fmaf(y0, y0, q1); q1 = fmaf(y1, y1, q1);
                        }
                }
                if (hw != 1) {
                    asm volatile("st.shared.v4.f32 [%0], {%1,%2,%3,%4};" ::"r"(SB + SM_ST + hw * 256 + lane * 16), "f"(s0), "f"(q0), "f"(s1), "f"(q1) : "memory");
                    asm volatile("bar.arrive 6, 96;" ::: "memory");
                } else {
                    asm volatile("bar.sync 6, 96;" ::: "memory");
                    uint32_t a[4], b[4];
                    lds128(a, SB + SM_ST + lane * 16); lds128(b, SB + SM_ST + 512 + lane * 16);
                    s0 = quad_sum(s0 + __uint_as_float(a[0]) + __uint_as_float(b[0])); q0 = quad_sum(q0 + __uint_as_float(a[1]) + __uint_as_float(b[1]));
                    s1 = quad_sum(s1 + __uint_as_float(a[2]) + __uint_as_float(b[2])); q1 = quad_sum(q1 + __uint_as_float(a[3]) + __uint_as_float(b[3]));
                    asm volatile("bar.arrive 7, 64;" ::: "memory");
                    const float m = ((lane & 1) ? s1 : s0) * (1.f / 512), q = ((lane & 1) ? q1 : q0) * (1.f / 512);
                    if (!(lane & 2)) stbox(gs + S_STAT + j * 16 + (lane >> 2) + (lane & 1) * 8, __float_as_uint(m), __float_as_uint(rsq(fmaxf(q - m * m, 0.f) + 1e-5f)), ep, 0);
                }
            }
            PROF(43);
            {
                float t[4] = {0.f, 0.f, 0.f, 0.f};
                gather8<24 * 16>(t, g_csq + (((lane >> 4) * 64 + j) * 3 + hw) * 16 + (lane & 15), tag);
#pragma unroll
                for (int i = 0; i < 4; i++) t[i] += __shfl_xor_sync(0xffffffffu, t[i], 16);
                if (lane < 16) asm volatile("st.shared.v4.f32 [%0], {%1,%2,%3,%4};" ::"r"(SB + SM_CSQ + hw * 256 + lane * 16), "f"(t[0]), "f"(t[1]), "f"(t[2]), "f"(t[3]) : "memory");
            }
            PROF(41);
            const uint32_t st = SB + SM_ST + hw * 512 + lane * 16;
            if (hw == 2 && lane == 0) asm volatile("st.shared.u32 [%0], %1;" ::"r"(bar + B_EP * 8), "r"(ep) : "memory");
            if (hw == 0) asm volatile("bar.sync 7, 64;" ::: "memory");
            __syncwarp();
            if (lane == 0) mbar_arrive(bar + B_CS1 * 8);
            PROF(44);
            if (hw == 2) {
                const uint4* q = reinterpret_cast<const uint4*>(P.wo + (j * 64 + g * 4) * 512) + lane;
                float t[4];
                uint4 v[8];
#pragma unroll
                for (int i = 0; i < 8; i++)
                    asm volatile("ld.global.nc.v4.u32 {%0,%1,%2,%3}, [%4];" : "=r"(v[i].x), "=r"(v[i].y), "=r"(v[i].z), "=r"(v[i].w) : "l"(q + i * 32) : "memory");
#pragma unroll
                for (int i = 0; i < 8; i++) {
                    const float a = ((blo(v[i].x) + bhi(v[i].x)) + (blo(v[i].y) + bhi(v[i].y))) + ((blo(v[i].z) + bhi(v[i].z)) + (blo(v[i].w) + bhi(v[i].w)));
                    if (i & 1) t[i >> 1] += a; else t[i >> 1] = a;
                }
#pragma unroll
                for (int o = 16; o; o >>= 1)
#pragma unroll
                    for (int i = 0; i < 4; i++) t[i] += __shfl_xor_sync(0xffffffffu, t[i], o);
                if (lane < 2)
                    stbox(g_wb + cta * 2 + lane, (__float_as_uint(t[0] * (1.f / 512)) & ~3u) | tag, __float_as_uint(t[1] * (1.f / 512)), __float_as_uint(t[2] * (1.f / 512)), __float_as_uint(t[3] * (1.f / 512)));
                if (lane < 16) {
                    uint32_t u[4];
                    int n = 0;
                    do ldbox(u, g_wb + (lane * 8 + j) * 2); while (((u[0] ^ tag) & 3u) && ++n < SPIN_LIMIT);
                    asm volatile("st.shared.v4.u32 [%0], {%1,%2,%3,%4};" ::"r"(SB + SM_WB + lane * 16), "r"(u[0]), "r"(u[1]), "r"(u[2]), "r"(u[3]) : "memory");
                }
                __syncwarp();
                if (lane == 0) mbar_arrive(bar + B_WB * 8);
                PROF(45);
                mbar_wait(bar + B_CS1 * 8, 0);
                if (lane == 0) *(reinterpret_cast<volatile unsigned*>(gs + S_EP) + j) = ep;
            } else {
#pragma unroll 1
                for (int i = 0; i < 2; i++) {
                    mbar_wait(bar + (i ? B_WD : B_OR) * 8, 0);
                    float2 t = sum_rows(gs + S_ROWS + i * 512 + hw * 32 + lane, ep);
                    if (i) { t.x = fmaf(t.x, 1.f / 512, 1e-5f); t.y = fmaf(t.y, 1.f / 512, 1e-5f); }
                    asm volatile("st.shared.v2.f32 [%0], {%1,%2};" ::"r"(st + i * 8), "f"(t.x), "f"(t.y) : "memory");
                    __syncwarp();
                    if (lane == 0) mbar_arrive(bar + (B_PM + i) * 8);
                    PROFE(46 + i);
                }
            }
        }
    } else {
        PROF_ROLE(PTID);
        asm volatile("setmaxnreg.inc.sync.aligned.u32 224;");
        unsigned ep;
        asm volatile("bar.sync 0, 320;" ::: "memory");
        PROFS(22);
        const uint32_t id0 = cta | tid << 8;
#define PHASE                                                                                                                        \
    uint32_t id_ = id0;                                                                                                              \
    asm volatile("" : "+r"(id_));                                                                                                    \
    const uint32_t idu_ = __shfl_sync(0xffffffffu, id_, 0);                                                    \
    [[maybe_unused]] const int cta = idu_ & 127, g = cta >> 3, j = cta & 7, gb = cta & ~7, qd = j & 1;                               \
    [[maybe_unused]] const int tid = id_ >> 8, lane = tid & 31, warp = idu_ >> 13, p = warp >> 2, w = warp & 3, r = lane >> 2, c = lane & 3; \
    [[maybe_unused]] uint4* const gs = g_scr + g * GRP;                                                                              \
    [[maybe_unused]] const int boxoff = warp * 128 + lane;                                                       \
    [[maybe_unused]] const int offA64 = qd ? 32 : 128, offA32 = qd ? 0 : 192, offB = qd ? 96 : 64, offC = qd ? 160 : 0;              \
                              \
    [[maybe_unused]] const uint32_t fragA = SB + SM_ACT + p * 8192 + (w * 16 + (lane & 15)) * 128 + (((lane >> 4) ^ (lane & 7)) << 4); \
    [[maybe_unused]] const uint32_t priv = SB + SM_ACT + p * 8192 + w * 2048 + lane * 16;         \
    [[maybe_unused]] const uint32_t rowst = SB + SM_ST + warp * 128 + r * 16;                    \
    [[maybe_unused]] uint4* const my_p = gs + S_P + (j * 8 + warp) * 448 + lane;                                                     \
    [[maybe_unused]] const uint4* const pq = gs + S_P + ((j ^ 4) * 8 + warp) * 448 + lane
#define FRAG(slot, ks) ((fragA ^ ((ks) * 32)) + (slot) * 16384)

        uint32_t res[4][4];
        uint32_t own[4][4];
        uint32_t tag;
        float mu0, mu1;
        {
            PHASE;
            float aq[32], akv[64];
            const uint64_t dR = P.dB128[0] + (SM_RING >> 4);
            uint32_t A0[4][4], A1[4][4];
            auto chunk = [&](uint32_t(&A)[4][4], uint32_t(&N)[4][4], int d, bool first, bool withQ, bool release, bool next) {
                const uint64_t b = dR + (d & 3) * 1536;
                mbar_wait(bar + (B_WF + (d & 3)) * 8, d >> 2);
                PROFD(32 + d);
                wg_fence();
#pragma unroll
                for (int k = 0; k < 4; k++) {
                    if (first && k == 0) { wgmma_rs_n128<false>(akv, A[0], b + 512); wgmma_rs_n64<false>(aq, A[0], b); }
                    else {
                        wgmma_rs_n128<true>(akv, A[k], b + 512 + k * 128);
                        if (withQ) wgmma_rs_n64<true>(aq, A[k], b + k * 128);
                    }
                    if (k == 3) wg_commit();
                    if (k == 2 && next) {
                        wg_commit();
                        if (!first) {
                            wg_wait<1>();
                            if (release && lane == 0) mbar_arrive(bar + (B_WE + ((d - 1) & 3)) * 8);
                        }
                        mbar_wait(bar + (B_XF + d + 1) * 8, 0);
#pragma unroll
                        for (int q = 0; q < 4; q++) ldsm4(N[q], FRAG(d + 1, q));
                        wg_fence();
                    }
                }
            };
            auto clear2 = [&](uint4* z) { clrbox(z); clrbox(z + 32); };
            uint4* const my_halo = gs + S_HALO + (j * 2 + p) * 128 + lane;
            PROFS(24);
            mbar_wait(bar + B_XF * 8, 0);
            PROFS(25);
#pragma unroll
            for (int k = 0; k < 4; k++) ldsm4(A0[k], FRAG(0, k));
            PROF(1);
            chunk(A0, A1, 0, true, true, false, true);
            if (w == 3) { clear2(my_halo); clear2(my_halo + 64); }
            if (c < 2) clrbox(gs + S_ROWS + c * 512 + j * 64 + warp * 8 + r);
#pragma unroll 1
            for (int d = 1; d < 5; d += 2) {
                uint4* z = gs + (d < 3 ? S_O : S_H) + j * 1024 + boxoff;
                chunk(A1, A0, d, false, true, true, true);
                clear2(z);
                chunk(A0, A1, d + 1, false, true, true, true);
                clear2(z + 64);
            }
            chunk(A1, A0, 5, false, false, true, true);
            chunk(A0, A1, 6, false, false, false, true);
            uint32_t sa[4], sb[4];
            const uint4* const sp = gs + S_STAT + warp * 16 + r;
            chunk(A1, A0, 7, false, false, false, false);
            ldbox(sa, sp); ldbox(sb, sp + 8);
#pragma unroll
            for (int k = 0; k < 4; k++) ldsm4(res[k], FRAG(j, k));
            auto mma_q = [&](int d) {
                wg_fence();
#pragma unroll
                for (int k = 0; k < 4; k++) wgmma_ss_n64<true>(aq, P.dA[0] + (SM_ACT >> 4) + p * 512 + d * 1024 + k * 2, dR + (d & 3) * 1536 + k * 128);
                wg_commit();
            };
            mma_q(5);
            PROF(20);
            mbar_wait(bar + B_CS1 * 8, 0);
            PROF(21);
            asm volatile("ld.shared.u32 %0, [%1];" : "=r"(ep) : "r"(bar + B_EP * 8) : "memory");
            for (int n = 0; __any_sync(0xffffffffu, ((sa[2] ^ ep) | (sb[2] ^ ep) | sa[3] | sb[3]) != 0) && n < SPIN_LIMIT; n++) { ldbox(sa, sp); ldbox(sb, sp + 8); }
            tag = (ep & 1) ? 1u : 0x10000u;
            const float rs0 = __uint_as_float(sa[1]), rs1 = __uint_as_float(sb[1]);
            mu0 = __uint_as_float(sa[0]); mu1 = __uint_as_float(sb[0]);
            const float n0 = -mu0 * rs0, n1 = -mu1 * rs1;
            wg_wait<1>();
            reg_fence<64>(akv);
            PROF(3);
            uint32_t K1[8], K2[8], V1[8], V2[8];
            float2 cs[16];
#pragma unroll
            for (int i = 0; i < 16; i++) {
                const float* a = akv + 4 * i;
                cs[i] = lds64(SB + SM_CSQ + 256 + i * 32 + c * 8);
                const uint32_t hi = pack2(fmaf(a[2], rs1, n1 * cs[i].x), fmaf(a[3], rs1, n1 * cs[i].y));
                if (i < 8) K2[i] = hi; else V2[i - 8] = movm(hi);
                if (i == 8) mma_q(6);
            }
            if (w == 3) {
#pragma unroll
                for (int h = 0; h < 4; h++) stbox(my_halo + h * 32, (K2[2 * h] & ~TAGM) | tag, K2[2 * h + 1], V2[2 * h], V2[2 * h + 1]);
            } else {
#pragma unroll
                for (int h = 0; h < 4; h++)
                    asm volatile("st.shared.v4.u32 [%0], {%1,%2,%3,%4};" ::"r"(priv + h * 512), "r"(K2[2 * h]), "r"(K2[2 * h + 1]), "r"(V2[2 * h]), "r"(V2[2 * h + 1]) : "memory");
            }
            __syncwarp();
            PROF(2);
            mma_q(7);
#pragma unroll
            for (int i = 0; i < 16; i++) {
                const float* a = akv + 4 * i;
                const uint32_t lo = pack2(fmaf(a[0], rs0, n0 * cs[i].x), fmaf(a[1], rs0, n0 * cs[i].y));
                if (i < 8) K1[i] = lo; else V1[i - 8] = movm(lo);
            }
            uint32_t prev[4][4];
#pragma unroll
            for (int i = 0; i < 8; i++) asm volatile("" : "+r"(K1[i]), "+r"(V1[i]));
            mbar_wait(bar + B_CS1 * 8, 0);
            if (w == 0 && g > 0) ldgroup(prev, my_halo - GRP);
            wg_wait<0>();
            reg_fence<32>(aq);
            if (lane == 0) {
                mbar_arrive(bar + (B_WE + 1) * 8);
                mbar_arrive(bar + (B_WE + 2) * 8);
                mbar_arrive_dep(bar + (B_WE + 3) * 8, res[0][0] | res[1][0] | res[2][0] | res[3][0]);
            }
            PROF(4);
            const float qs = 0.25f * 1.4426950408889634f;
            const float rq0 = rs0 * qs, rq1 = rs1 * qs, nq0 = n0 * qs, nq1 = n1 * qs;
            uint32_t Q[4][4];
#pragma unroll
            for (int i = 0; i < 8; i++) {
                const float2 cs = lds64(SB + SM_CSQ + i * 32 + c * 8);
                Q[i >> 1][(i & 1) * 2] = pack2(fmaf(aq[4 * i], rq0, nq0 * cs.x), fmaf(aq[4 * i + 1], rq0, nq0 * cs.y));
                Q[i >> 1][(i & 1) * 2 + 1] = pack2(fmaf(aq[4 * i + 2], rq1, nq1 * cs.x), fmaf(aq[4 * i + 3], rq1, nq1 * cs.y));
            }
            float S1[4][4], S2[4][4];
#pragma unroll
            for (int h = 0; h < 4; h++) {
                mma16(S1[h], Q[h][0], Q[h][1], Q[h][2], Q[h][3], K1[2 * h], K1[2 * h + 1]);
                mma16(S2[h], Q[h][0], Q[h][1], Q[h][2], Q[h][3], K2[2 * h], K2[2 * h + 1]);
            }
            asm volatile("bar.sync %0, 128;" ::"r"(1 + p) : "memory");
            if (w == 0) {
                if (g > 0) chkgroup(prev, my_halo - GRP, tag);
                else {
#pragma unroll
                    for (int h = 0; h < 4; h++) prev[h][0] = prev[h][1] = prev[h][2] = prev[h][3] = 0;
                }
            } else {
#pragma unroll
                for (int h = 0; h < 4; h++) lds128(prev[h], priv - 2048 + h * 512);
            }
            PROF(5);
            const bool up0 = 2 * c > r, up1 = 2 * c + 1 > r;
            const uint32_t M = (up0 ? 0xffffu : 0u) | (up1 ? 0xffff0000u : 0u);
            const float nb = (g == 0 && w == 0) ? -1e9f * 1.4426950408889634f : 0.f;
#pragma unroll
            for (int h = 0; h < 4; h++) {
                float S0[4];
                mma16(S0, Q[h][0], Q[h][1], Q[h][2], Q[h][3], prev[h][0], prev[h][1], nb);
                const float a0 = up0 ? S0[0] : S1[h][0], a1 = up1 ? S0[1] : S1[h][1];
                const float b0 = up0 ? S1[h][2] : S2[h][2], b1 = up1 ? S1[h][3] : S2[h][3];
                float ma = fmaxf(a0, a1), mb = fmaxf(b0, b1);
                ma = fmaxf(ma, __shfl_xor_sync(0xffffffffu, ma, 1)); mb = fmaxf(mb, __shfl_xor_sync(0xffffffffu, mb, 1));
                ma = fmaxf(ma, __shfl_xor_sync(0xffffffffu, ma, 2)); mb = fmaxf(mb, __shfl_xor_sync(0xffffffffu, mb, 2));
                const float ea0 = ex2(a0 - ma), ea1 = ex2(a1 - ma), eb0 = ex2(b0 - mb), eb1 = ex2(b1 - mb);
                const float ia = rcp(quad_sum(ea0 + ea1)), ib = rcp(quad_sum(eb0 + eb1));
                const uint32_t P0 = pack2(ea0 * ia, ea1 * ia), P1 = pack2(eb0 * ib, eb1 * ib);
#pragma unroll
                for (int D = 0; D < 2; D++) {
                    float O[4];
                    mma16(O, P0 & M, 0u, P0 & ~M, P1 & M, prev[h][2 + D], V1[2 * h + D]);
                    mma8(O, 0u, P1 & ~M, V2[2 * h + D]);
                    own[h][2 * D] = pack2(O[0], O[1]);
                    own[h][2 * D + 1] = pack2(O[2], O[3]);
                }
                own[h][0] = (own[h][0] & ~TAGM) | tag;
                stbox(gs + S_O + j * 1024 + boxoff + h * 32, own[h][0], own[h][1], own[h][2], own[h][3]);
            }
            PROF(6);
        }
#define SRC(box, d) (gs + (box) + kc_at(j, d) * 1024 + boxoff)
        float ao[32];
        {
            PHASE;
            uint32_t in[7][4][4];
            const uint64_t b = P.dB128[0] + ((SM_ACT + 16384) >> 4);
            {
                mbar_wait(bar + B_WB * 8, 0);
                float a0 = 0.f, a1 = 0.f;
#pragma unroll
                for (int i = 0; i < 8; i++) {
                    const float2 wb = lds64(SB + SM_WB + i * 32 + c * 8);
                    const uint32_t xa = own[i >> 1][(i & 1) * 2], xb = own[i >> 1][(i & 1) * 2 + 1];
                    a0 = fmaf(blo(xa), wb.x, a0); a0 = fmaf(bhi(xa), wb.y, a0);
                    a1 = fmaf(blo(xb), wb.x, a1); a1 = fmaf(bhi(xb), wb.y, a1);
                }
                put_rows(gs + S_ROWS + j * 64 + warp * 8 + r, c, a0, a1, ep);
            }
#pragma unroll
            for (int i = 0; i < 8; i++) {
                const uint32_t xa = res[i >> 1][(i & 1) * 2], xb = res[i >> 1][(i & 1) * 2 + 1];
                ao[4 * i] = blo(xa) - mu0; ao[4 * i + 1] = bhi(xa) - mu0; ao[4 * i + 2] = blo(xb) - mu1; ao[4 * i + 3] = bhi(xb) - mu1;
            }
            mbar_wait(bar + B_OF * 8, 0);
            wg_fence();
#pragma unroll
            for (int k = 0; k < 4; k++) wgmma_rs_n64<true>(ao, own[k], b + j * 512 + k * 128);
            wg_commit();
            asm volatile("bar.sync %0, 128;" ::"r"(1 + p) : "memory");
            pollgroup(in[0], SRC(S_O, 1), tag);
            PROF(7);
            auto cp_in = [&](int e) {
                const uint4* src = SRC(S_O, e);
#pragma unroll
                for (int i = 0; i < 4; i++) asm volatile("cp.async.cg.shared.global [%0], [%1], 16;" ::"r"(priv + oland(e) + i * 512), "l"(src + i * 32) : "memory");
                if (e & 1) asm volatile("cp.async.commit_group;" ::: "memory");
            };
            auto lds_in = [&](int e) {
#pragma unroll
                for (int i = 0; i < 4; i++) lds128(in[e - 1][i], priv + oland(e) + i * 512);
            };
            auto mma_o = [&](int d) {
                if (d == 2 && lane == 0) mbar_arrive(bar + B_OR * 8);
                PROFD(20 + d);
                wg_fence();
#pragma unroll
                for (int k = 0; k < 4; k++) wgmma_rs_n64<true>(ao, in[d - 1][k], b + kc_at(j, d) * 512 + k * 128);
                wg_commit();
            };
            cp_in(2); cp_in(3);
            mma_o(1);
            cp_in(4); cp_in(5);
            asm volatile("cp.async.wait_group 1;" ::: "memory");
            lds_in(2); lds_in(3);
            chkgroup(in[1], SRC(S_O, 2), tag); chkgroup(in[2], SRC(S_O, 3), tag);
            mma_o(2);
            asm volatile("cp.async.wait_group 0;" ::: "memory");
            lds_in(4); lds_in(5);
            mma_o(3);
            chkgroup(in[3], SRC(S_O, 4), tag); chkgroup(in[4], SRC(S_O, 5), tag);
            ldgroup(in[5], SRC(S_O, 6));
            ldgroup(in[6], SRC(S_O, 7));
            mma_o(4); mma_o(5);
            mbar_wait(bar + B_OF * 8, 0);
            chkgroup(in[5], SRC(S_O, 6), tag); chkgroup(in[6], SRC(S_O, 7), tag);
            mma_o(6); mma_o(7);
            mbar_wait(bar + B_PM * 8, 0);
            const float2 ma = lds64(rowst);
            const float ma0 = ma.x, ma1 = ma.y;
            mu0 += ma0; mu1 += ma1;
            wg_wait<0>();
            reg_fence<32>(ao);
            asm volatile("bar.arrive %0, 256;" ::"r"(3 + p) : "memory");
            PROF(8);
#pragma unroll
            for (int i = 0; i < 8; i++) { ao[4 * i] -= ma0; ao[4 * i + 1] -= ma0; ao[4 * i + 2] -= ma1; ao[4 * i + 3] -= ma1; }
            pack_frag(own, ao);
            __syncwarp();
#pragma unroll
            for (int k = 0; k < 4; k++) stsm4(FRAG(0, k), own[k]);
            stgroup(gs + S_H + j * 1024 + boxoff, own, tag);
        }
        float aB[64];
        float k0, k1, v0, v1;
        uint32_t Po[14][4], Pr[14][4];
#define GLU(acc, uoff, t, T0)                                                                                          \
    do {                                                                                                               \
        uint32_t(&F)[4] = Po[(T0) + ((t) >> 1)];                                                                       \
        glu_tile((acc) + 4 * (t), (acc) + (uoff) + 4 * (t), k0, k1, v0, v1, F[((t) & 1) * 2], F[((t) & 1) * 2 + 1]);   \
        if ((t) & 1) { F[0] = (F[0] & ~TAGM) | tag; stbox(my_p + ((T0) + ((t) >> 1)) * 32, F[0], F[1], F[2], F[3]); } \
    } while (0)
        {
            float aA[64], aH[32];
          {
            PHASE;
            uint32_t in[4][4][4];
            const uint64_t dH = P.dB64 + ((SM_RING + 16384) >> 4), dR = P.dB128[1] + (SM_RING >> 4);
            mbar_wait(bar + B_WF * 8, 0);
            PROF(9);
            wg_fence();
#pragma unroll
            for (int k = 0; k < 4; k++) {
                if (k == 0) { wgmma_rs_n128<false>(aA, own[0], dR); wgmma_rs_n64<false>(aH, own[0], dH); }
                else { wgmma_rs_n128<true>(aA, own[k], dR + k * 128); wgmma_rs_n64<true>(aH, own[k], dH + k * 64); }
            }
            wg_commit();
            float q0 = 0.f, q1 = 0.f;
#pragma unroll
            for (int i = 0; i < 8; i++) {
                q0 = fmaf(ao[4 * i], ao[4 * i], q0); q0 = fmaf(ao[4 * i + 1], ao[4 * i + 1], q0);
                q1 = fmaf(ao[4 * i + 2], ao[4 * i + 2], q1); q1 = fmaf(ao[4 * i + 3], ao[4 * i + 3], q1);
            }
            put_rows(gs + S_ROWS + 512 + j * 64 + warp * 8 + r, c, q0, q1, ep);
            pollgroup(in[0], SRC(S_H, 1), tag);
            PROF(10);
#define HBUF(d) ((d) == 5 ? own : in[(d) < 5 ? (d) - 1 : (d) - 6])
#pragma unroll
            for (int d = 1; d < 8; d++) {
                uint32_t(&a)[4][4] = HBUF(d);
                mbar_wait(bar + (B_WF + (d & 3)) * 8, d >> 2);
                if (d > 1 && !(d & 1)) { chkgroup(a, SRC(S_H, d), tag); chkgroup(HBUF(d + 1), SRC(S_H, d + 1), tag); }
                if (d == 1) { ldgroup(HBUF(2), SRC(S_H, 2)); ldgroup(HBUF(3), SRC(S_H, 3)); }
                if (d == 2 || d == 4) ldgroup(HBUF(d + 2), SRC(S_H, d + 2));
                if (d == 1) asm volatile("bar.sync %0, 256;" ::"r"(4 - p) : "memory");
#pragma unroll
                for (int k = 0; k < 4; k++) stsm4(FRAG(d, k), a[k]);
                PROFD(48 + d);
                wg_fence();
#pragma unroll
                for (int k = 0; k < 4; k++) {
                    wgmma_rs_n128<true>(aA, a[k], dR + (d & 3) * 1536 + k * 128);
                    wgmma_rs_n64<true>(aH, a[k], dH + (d & 3) * 1536 + k * 64);
                }
                wg_commit();
                if (d == 2 || d == 4) ldgroup(HBUF(d + 3), SRC(S_H, d + 3));
                wg_wait<1>();
                if (lane == 0) mbar_arrive(bar + (B_WE + ((d - 1) & 3)) * 8);
                if (d == 5 && lane == 0) mbar_arrive(bar + B_WD * 8);
            }
            mbar_wait(bar + B_L2 * 8, 0);
            const float2 vv = lds64(rowst + 8);
            v0 = vv.x; v1 = vv.y;
            k0 = -1.4426950408889634f * rsq(v0); k1 = -1.4426950408889634f * rsq(v1);
            asm volatile("fence.proxy.async.shared::cta;" ::: "memory");
            asm volatile("bar.sync %0, 128;" ::"r"(1 + p) : "memory");
            PROF(11);
          }
            PHASE;
            const uint64_t dA = P.dA[0] + (SM_ACT >> 4) + p * 512, dRB = P.dB128[2] + (SM_RING >> 4);
#pragma unroll
            for (int d = 0; d < 8; d++) {
                mbar_wait(bar + (B_GF + d % 6) * 8, (d / 6) & 1);
                if (d == 0 && p == 1) asm volatile("bar.sync 5, 256;" ::: "memory");
                wg_fence();
#pragma unroll
                for (int k = 0; k < 4; k++) {
                    if (d == 0 && k == 0) wgmma_ss_n128<false>(aB, dA, dRB);
                    else wgmma_ss_n128<true>(aB, dA + d * 1024 + k * 2, dRB + d % 6 * 1024 + k * 128);
                    if (d >= 1 && d < 7 && (k & 1)) {
                        wg_commit();
                        const int t = (d - 1) * 2 + (k >> 1);
                        if (t < 8) GLU(aA, 32, t, 0); else GLU(aH, 16, t - 8, 4);
                    }
                }
                if (d == 0 || d == 7) { wg_commit(); wg_wait<1>(); } else wg_wait<2>();
                if (lane == 0) mbar_arrive(bar + (d == 0 ? B_WE + 3 : B_GE + (d - 1) % 6) * 8);
                if (d >= 4) clrbox(my_p + (6 + d) * 32);
                if (d == 1 && p == 0) asm volatile("bar.arrive 5, 256;" ::: "memory");
                if (d == 0) { reg_fence<64>(aA); reg_fence<32>(aH); }
            }
        }
        float aD0[32], aD1[32];
#define PBAD(T0, N) [&] { uint32_t bad = 0; _Pragma("unroll") for (int i = T0; i < T0 + N; i++) bad |= Pr[i][0] ^ tag; return __any_sync(0xffffffffu, (bad & TAGM) != 0); }()
#define PCHK(T0, N)                                                                                                    \
    if (__builtin_expect(PBAD(T0, N), 0)) {                                                                            \
        int n = 0;                                                                                                     \
        do { _Pragma("unroll") for (int i = T0; i < T0 + N; i++) ldbox(Pr[i], pq + i * 32); } while (PBAD(T0, N) && ++n < SPIN_LIMIT); \
    }
#define KOFF(t) ((t) < 4 ? dWA + (t) * 128 : (t) < 6 ? dWH + ((t) - 4) * 128 : (t) < 10 ? dWB + ((t) - 6) * 128 : dWC + ((t) - 10) * 128)
#define DMMA(acc, F, tile, T0, T1, FIRST)                                                                              \
    do {                                                                                                               \
        wg_fence();                                                                                                    \
        _Pragma("unroll") for (int t = T0; t < T1; t++) {                                                              \
            if (FIRST == 1 && t == T0) wgmma_rs_n64<false>(acc, F[t], KOFF(t) + dtile(tile) * 64);                     \
            else if (FIRST == 2 && t == T0) wgmma_rs_n64_reuse(acc, F[t], KOFF(t) + dtile(tile) * 64);                 \
            else wgmma_rs_n64<true>(acc, F[t], KOFF(t) + dtile(tile) * 64);                                            \
        }                                                                                                              \
        wg_commit();                                                                                                   \
    } while (0)
#define DWAIT(tile) mbar_wait(bar + (B_DF + (tile)) * 8, 0)
        {
            PHASE;
            float aC[64];
            const uint64_t dA = P.dA[1] + (SM_ACT >> 4) + p * 512, dR = P.dB128[3] + (SM_RING >> 4);
#pragma unroll
            for (int d = 0; d < 8; d++) {
                const int n = 8 + d;
                mbar_wait(bar + (B_GF + n % 6) * 8, (n / 6) & 1);
                wg_fence();
#pragma unroll
                for (int k = 0; k < 4; k++) {
                    if (d == 0 && k == 0) wgmma_ss_n128<false>(aC, dA, dR + n % 6 * 1024);
                    else wgmma_ss_n128<true>(aC, dA + d * 1024 + k * 2, dR + n % 6 * 1024 + k * 128);
                }
                wg_commit();
                wg_wait<1>();
                if (lane == 0) mbar_arrive(bar + (B_GE + (n - 1) % 6) * 8);
                if (d == 0) reg_fence<64>(aB);
                if (d == 4 || d == 5) {
                    uint4* z = gs + S_PART + (((j & 4) + ((j + 3) & 3)) * 3 + 2) * 1024 + boxoff + (d & 1) * 64;
                    clrbox(z); clrbox(z + 32);
                }
                if (d == 5) {
#pragma unroll
                    for (int i = 0; i < 6; i++) ldbox(Pr[i], pq + i * 32);
                }
                GLU(aB, 32, d, 6);
            }
            const uint64_t dWA = P.dB128[0] + offA64 * 8, dWH = P.dB128[0] + offA32 * 8, dWB = P.dB128[0] + offB * 8, dWC = P.dB128[0] + offC * 8;
            DWAIT(0);
            DMMA(aD0, Po, 0, 0, 2, 1);
            wg_wait<1>();
            reg_fence<64>(aC);
            if (lane == 0) mbar_arrive(bar + (B_GE + 3) * 8);
            PROF(14);
            DMMA(aD0, Po, 0, 2, 6, 0);
            GLU(aC, 32, 0, 10); GLU(aC, 32, 1, 10);
            DMMA(aD0, Po, 0, 6, 10, 0);
            GLU(aC, 32, 2, 10); GLU(aC, 32, 3, 10);
            DWAIT(1);
            PCHK(0, 6);
            DMMA(aD0, Pr, 1, 0, 3, 0);
            GLU(aC, 32, 4, 10); GLU(aC, 32, 5, 10);
            DMMA(aD0, Pr, 1, 3, 6, 0);
            GLU(aC, 32, 6, 10); GLU(aC, 32, 7, 10);
            DWAIT(2);
            DMMA(aD1, Po, 2, 0, 10, 1);
            DWAIT(2);
#pragma unroll
            for (int i = 6; i < 14; i++) ldbox(Pr[i], pq + i * 32);
            DWAIT(3);
            DMMA(aD1, Pr, 3, 0, 6, 0);
            DMMA(aD0, Po, 0, 10, 14, 0);
            DMMA(aD1, Po, 2, 10, 14, 0);
        }
        PROF(15);
        {
            PHASE;
            const uint64_t dWA = P.dB128[1] + offA64 * 8, dWH = P.dB128[1] + offA32 * 8, dWB = P.dB128[1] + offB * 8, dWC = P.dB128[1] + offC * 8;
            uint4* const out0 = gs + S_PART + (j & 4) * 3072 + boxoff;
            const uint4* const inbox = gs + S_PART + j * 3072 + boxoff;
            auto ship = [&](float(&a)[32], int o) {
                reg_fence<32>(a);
                pack_frag(own, a);
                stgroup(out0 + ((j + 1 + o) & 3) * 3072 + o * 1024, own, tag);
            };
            DWAIT(3);
            PCHK(6, 8);
            DMMA(aD0, Pr, 1, 6, 14, 0);
            DMMA(aD1, Pr, 3, 6, 14, 0);
            wg_wait<1>();
            if (lane == 0) mbar_arrive(bar + B_DE * 8);
            ship(aD0, 0);
            DWAIT(4);
            DMMA(aD0, Po, 4, 0, 4, 2);
            wg_wait<1>();
            ship(aD1, 1);
            PROF(16);
            DMMA(aD0, Po, 4, 4, 14, 0);
            DWAIT(5);
            DMMA(aD0, Pr, 5, 0, 14, 0);
            DWAIT(6);
            DMMA(aD1, Po, 6, 0, 4, 2);
            wg_wait<1>();
            ship(aD0, 2);
            PROF(13);
            float sum[32];
#pragma unroll
            for (int k = 0; k < 4; k++) ldsm4(own[k], FRAG(0, k));
            DMMA(aD1, Po, 6, 4, 8, 0);
#pragma unroll
            for (int i = 0; i < 16; i++) { sum[2 * i] = blo(own[i >> 2][i & 3]) + ((i & 1) ? mu1 : mu0); sum[2 * i + 1] = bhi(own[i >> 2][i & 3]) + ((i & 1) ? mu1 : mu0); }
            reg_fence<32>(sum);
            ldgroup(own, inbox);
            DMMA(aD1, Po, 6, 8, 14, 0);
            DWAIT(7);
            DMMA(aD1, Pr, 7, 0, 3, 0);
            wg_wait<1>();
            chkgroup(own, inbox, tag);
            uint32_t in2[4][4];
            ldgroup(res, inbox + 1024);
            ldgroup(in2, inbox + 2048);
            add_frag(sum, own);
            DMMA(aD1, Pr, 7, 3, 14, 0);
            DWAIT(7);
            chkgroup(res, inbox + 1024, tag);
            add_frag(sum, res);
            wg_wait<0>();
            reg_fence<32>(aD1);
            PROF(18);
#pragma unroll
            for (int i = 0; i < 32; i++) sum[i] += aD1[i];
            pack_frag(own, sum);
            __nv_bfloat16* const op = P.out + (size_t)(g * 128 + 2 * (w * 16 + (lane >> 3)) + p) * 512 + j * 64 + (lane & 7) * 8;
#pragma unroll
            for (int k = 0; k < 4; k++) asm volatile("" : "+r"(own[k][0]), "+r"(own[k][1]), "+r"(own[k][2]), "+r"(own[k][3]));
            DWAIT(7);
            chkgroup(in2, inbox + 2048, tag);
            PROF(17);
#pragma unroll
            for (int i = 0; i < 16; i++) own[i >> 2][i & 3] = badd2(own[i >> 2][i & 3], in2[i >> 2][i & 3]);
#pragma unroll
            for (int k = 0; k < 4; k++) stsm4(FRAG(0, k), own[k]);
            __syncwarp();
#pragma unroll
            for (int i = 0; i < 4; i++) {
                const int row = i * 4 + (lane >> 3);
                uint32_t v[4];
                lds128(v, SB + SM_ACT + p * 8192 + (w * 16 + row) * 128 + (((lane & 7) ^ (row & 7)) << 4));
                *reinterpret_cast<uint4*>(op + i * 4096) = make_uint4(v[0], v[1], v[2], v[3]);
            }
            PROF(19); PROFT(63); PROF_END;
        }
    }
}

typedef CUresult (*EncodeFn)(CUtensorMap*, CUtensorMapDataType, cuuint32_t, void*, const cuuint64_t*, const cuuint64_t*, const cuuint32_t*,
                             const cuuint32_t*, CUtensorMapInterleave, CUtensorMapSwizzle, CUtensorMapL2promotion, CUtensorMapFloatOOBfill);

void make_map(EncodeFn enc, CUtensorMap* m, const void* ptr, uint64_t cols, uint64_t rows, uint32_t bc, uint32_t br, CUtensorMapSwizzle sw,
              CUtensorMapL2promotion promo = CU_TENSOR_MAP_L2_PROMOTION_L2_128B) {
    cuuint64_t dims[2] = {cols, rows}, strides[1] = {cols * 2};
    cuuint32_t box[2] = {bc, br}, es[2] = {1, 1};
    enc(m, CU_TENSOR_MAP_DATA_TYPE_BFLOAT16, 2, const_cast<void*>(ptr), dims, strides, box, es, CU_TENSOR_MAP_INTERLEAVE_NONE, sw,
        promo, CU_TENSOR_MAP_FLOAT_OOB_FILL_NONE);
}

void make_map3(EncodeFn enc, CUtensorMap* m, const void* ptr, uint64_t rows, uint64_t parts) {
    cuuint64_t dims[3] = {512, rows, parts}, strides[2] = {parts * 1024, 1024};
    cuuint32_t box[3] = {64, 64, (cuuint32_t)parts}, es[3] = {1, 1, 1};
    CUresult r = enc(m, CU_TENSOR_MAP_DATA_TYPE_BFLOAT16, 3, const_cast<void*>(ptr), dims, strides, box, es, CU_TENSOR_MAP_INTERLEAVE_NONE,
        CU_TENSOR_MAP_SWIZZLE_128B, CU_TENSOR_MAP_L2_PROMOTION_L2_128B, CU_TENSOR_MAP_FLOAT_OOB_FILL_NONE);
    (void)r;
}

}

extern "C" void kernel_launch(void* const* d_in, const int* in_sizes, int n_in, void* d_out, int out_size) {
    static EncodeFn enc = nullptr;
    static int n_sm = 0;
    if (!enc) {
        int dev = 0;
        cudaGetDevice(&dev);
        cudaDeviceGetAttribute(&n_sm, cudaDevAttrMultiProcessorCount, dev);
        void* fn = nullptr;
        cudaDriverEntryPointQueryResult qr;
        cudaGetDriverEntryPoint("cuTensorMapEncodeTiled", &fn, cudaEnableDefault, &qr);
        enc = (EncodeFn)fn;
        cudaFuncSetAttribute(fused_block_kernel<true>, cudaFuncAttributeMaxDynamicSharedMemorySize, SMEM_BYTES);
        cudaFuncSetAttribute(fused_block_kernel<false>, cudaFuncAttributeMaxDynamicSharedMemorySize, SMEM_BYTES);
    }
    Params P;
    P.x = (const __nv_bfloat16*)d_in[0];
    P.wqkv = (const __nv_bfloat16*)d_in[1]; P.wo = (const __nv_bfloat16*)d_in[2];
    P.w1 = (const __nv_bfloat16*)d_in[4]; P.w3 = (const __nv_bfloat16*)d_in[5]; P.w2 = (const __nv_bfloat16*)d_in[6];
    P.out = (__nv_bfloat16*)d_out;
    make_map3(enc, &P.tmX, P.x, 1024, 2);
    make_map3(enc, &P.tmQKV, P.wqkv, 512, 3);
    make_map(enc, &P.tmWO, P.wo, 512, 512, 64, 256, CU_TENSOR_MAP_SWIZZLE_128B);
    make_map(enc, &P.tmW1, P.w1, 1792, 512, 64, 64, CU_TENSOR_MAP_SWIZZLE_128B);
    make_map(enc, &P.tmW3, P.w3, 1792, 512, 64, 64, CU_TENSOR_MAP_SWIZZLE_128B);
    make_map(enc, &P.tmW1h, P.w1, 1792, 512, 32, 64, CU_TENSOR_MAP_SWIZZLE_64B);
    make_map(enc, &P.tmW3h, P.w3, 1792, 512, 32, 64, CU_TENSOR_MAP_SWIZZLE_64B);
    make_map(enc, &P.tmW2, P.w2, 512, 1792, 64, 224, CU_TENSOR_MAP_SWIZZLE_128B);
    auto desc = [](uint64_t lbo, uint64_t sbo, uint64_t mode) { return (uint64_t)(SB >> 4) | (lbo >> 4) << 16 | (sbo >> 4) << 32 | mode << 62; };
    for (int i = 0; i < 4; i++) P.dB128[i] = desc(8192, 1024, 1);
    P.dB64 = desc(4096, 512, 2);
    P.dA[0] = P.dA[1] = desc(16, 1024, 1);
    if (n_sm == 132) fused_block_kernel<true><<<132, 384, SMEM_BYTES>>>(P);
    else fused_block_kernel<false><<<128, 384, SMEM_BYTES>>>(P);
}
```
